```python
import torch

def _softmax(x, axis=-1):
    return torch.softmax(x, dim=axis)
def _gelu(x):
    return torch.nn.functional.gelu(x, approximate="tanh")
def _silu(x):
    return torch.nn.functional.silu(x)
def _sigmoid(x):
    return torch.sigmoid(x)
def _layernorm(x, axis=-1, eps=1e-5):
    m = x.mean(dim=axis, keepdim=True)
    v = x.var(dim=axis, keepdim=True, unbiased=False)
    return (x - m) / torch.sqrt(v + eps)
def _scatter_add(tgt, idx, src, axis=0):
    return tgt.clone().index_add_(axis, idx, src)
def _segment_sum(src, seg, n):
    out = torch.zeros((n,) + src.shape[1:], dtype=src.dtype)
    return out.index_add_(0, seg, src)
def _pad(x, pw):
    flat = tuple(v for pair in reversed(pw) for v in pair)
    return torch.nn.functional.pad(x, flat)

kernel_name = 'sequential_preLN__spectral_fnet__geglu_ffn__prompt'

def setup_inputs():

    _w = (lambda a: (lambda t: t.to(torch.bfloat16) if t.is_floating_point() else t)(torch.as_tensor(a)))
    def _A_setup():
        B, S, D = 1, 2048, 640
        ns = torch.arange(S)[:, None] * torch.arange(S)[None, :]
        nd = torch.arange(D)[:, None] * torch.arange(D)[None, :]
        Ws_re = torch.cos(-2.0 * torch.pi * ns / S).to(float)
        Ws_im = torch.sin(-2.0 * torch.pi * ns / S).to(float)
        Wd_re = torch.cos(-2.0 * torch.pi * nd / D).to(float)
        Wd_im = torch.sin(-2.0 * torch.pi * nd / D).to(float)
        return {
            "x": _w((lambda *s: torch.randn(*s, dtype=torch.bfloat16) * 0.05)(B, S, D)),
            "dft_seq_re": _w(Ws_re),
            "dft_seq_im": _w(Ws_im),
            "dft_hid_re": _w(Wd_re),
            "dft_hid_im": _w(Wd_im),
        }
    _A_in = _A_setup()

    def _B_setup():
        B, S, D, F = 1, 2048, 640, 1728
        return {
            "x": _w((lambda *s: torch.randn(*s, dtype=torch.bfloat16) * 0.05)(B, S, D)),
            "w_gate": _w((lambda *s: torch.randn(*s, dtype=torch.bfloat16) * 0.2)(D, F)),
            "w_up": _w((lambda *s: torch.randn(*s, dtype=torch.bfloat16) * 0.2)(D, F)),
            "w_down": _w((lambda *s: torch.randn(*s, dtype=torch.bfloat16) * 0.2)(F, D)),
        }
    _B_in = _B_setup()

    return {
        "A_x": _A_in["x"],
        "A_dft_seq_re": _A_in["dft_seq_re"],
        "A_dft_seq_im": _A_in["dft_seq_im"],
        "A_dft_hid_re": _A_in["dft_hid_re"],
        "A_dft_hid_im": _A_in["dft_hid_im"],
        "B_x": _B_in["x"],
        "B_w_gate": _B_in["w_gate"],
        "B_w_up": _B_in["w_up"],
        "B_w_down": _B_in["w_down"],
    }

def reference(A_x, A_dft_seq_re, A_dft_seq_im, A_dft_hid_re, A_dft_hid_im, B_x, B_w_gate, B_w_up, B_w_down):
    def _A_ref(x, dft_seq_re, dft_seq_im, dft_hid_re, dft_hid_im):
        a = torch.einsum("bsd,ed->bse", x, dft_hid_re)
        b = torch.einsum("bsd,ed->bse", x, dft_hid_im)
        y = torch.einsum("ts,bse->bte", dft_seq_re, a) - torch.einsum("ts,bse->bte", dft_seq_im, b)
        return y

    def _B_ref(x, w_gate, w_up, w_down):
        return (_gelu(x @ w_gate) * (x @ w_up)) @ w_down

    x = A_x
    h = x + _A_ref(_layernorm(x, axis=-1), A_dft_seq_re, A_dft_seq_im, A_dft_hid_re, A_dft_hid_im)
    h2 = h + _B_ref(_layernorm(h, axis=-1), B_w_gate, B_w_up, B_w_down)
    return h2
```

```cpp
#include <cuda_runtime.h>
#include <cuda_bf16.h>
#include <cuda.h>
#include <stdint.h>

#define TRACE 0

namespace {

constexpr int S_ = 2048, D_ = 640, F_ = 1728;
constexpr int NCTA = 128;
constexpr float LN_EPS = 1e-5f;

__device__ __align__(1024) __nv_bfloat16 g_abt[1280 * 2048];
__device__ __align__(1024) __nv_bfloat16 g_h[S_ * D_];
__device__ __align__(1024) __nv_bfloat16 g_act[S_ * F_];
__device__ __align__(128) float2 g_stats1[S_];
__device__ __align__(128) float2 g_stats2[S_];
__device__ __align__(128) float g_rowsum[1280];
__device__ __align__(128) float g_colsum[2 * F_];
constexpr int FL_AB = 0;
constexpr int FL_S1 = FL_AB + 128;
constexpr int FL_RS = FL_S1 + 8;
constexpr int FL_H = FL_RS + 16;
constexpr int FL_S2 = FL_H + 16;
constexpr int FL_CS = FL_S2 + 16;
constexpr int FL_ACT = FL_CS + 8;
constexpr int FL_N = FL_ACT + 16 * 27;
__device__ __align__(128) unsigned g_flags[FL_N * 8];
__device__ unsigned g_epoch[NCTA];

struct Params {
    CUtensorMap x_a, wd_b[2], abt_st, abt_ld, ws_a[2], h_w, h_n, wg_b, wu_b, act_m, wdn_w, wdn_n, out_w, out_n;
    const __nv_bfloat16 *x, *wd[2], *ws[2], *wg, *wu, *wdn;
    __nv_bfloat16* out;
};

constexpr uint32_t SLOT = 16384;
constexpr uint32_t Z0 = 13 * SLOT;
constexpr uint32_t ZS1_1 = 12 * SLOT, ZS1_0 = 12 * SLOT + 10240;
constexpr uint32_t MISC = 14 * SLOT;
constexpr uint32_t SM_STATS = MISC;
constexpr uint32_t SM_RS = MISC + 2048;
constexpr uint32_t BAR = MISC + 2048 + 320;
constexpr uint32_t B_FULL = BAR, B_EMPTY = B_FULL + 40, B_FULLB1 = B_EMPTY + 40, B_FULLH = B_FULLB1 + 40,
                   B_EMPTYH = B_FULLH + 80, B_FULLW = B_EMPTYH + 80, B_EMPTYW = B_FULLW + 24, B_FULL5 = B_EMPTYW + 24,
                   B_EMPTY5 = B_FULL5 + 32, B_ORD = B_EMPTY5 + 32, B_EPI = B_ORD + 16, B_ZFULL = B_EPI + 16,
                   B_ZEMPTY = B_ZFULL + 16, B_STAT = B_ZEMPTY + 16, B_END = B_STAT + 16;
constexpr uint32_t SMEM_BYTES = 232448;
static_assert(B_END <= SMEM_BYTES, "smem");

__device__ __forceinline__ uint32_t ringA(int b) { int f = b + 3; if (f >= 5) f -= 5; return (7 + f) * SLOT; }
__device__ __forceinline__ uint32_t ringB(int b) { int f = b + 3; if (f >= 5) f -= 5; return f * 20480; }
__device__ __forceinline__ uint32_t hslot(int j) { return (uint32_t)((0x65B43A210Cull >> (4 * j)) & 15) * SLOT; }
__device__ __forceinline__ uint32_t a5slot(int s) { return (uint32_t)((0x6BAC >> (4 * s)) & 15) * SLOT; }

__device__ __forceinline__ uint32_t smem_u32(const void* p) { return (uint32_t)__cvta_generic_to_shared(p); }
__device__ __forceinline__ void mbar_init(uint32_t bar, uint32_t cnt) { asm volatile("mbarrier.init.shared::cta.b64 [%0], %1;" ::"r"(bar), "r"(cnt)); }
__device__ __forceinline__ void mbar_expect_tx(uint32_t bar, uint32_t bytes) { asm volatile("mbarrier.arrive.expect_tx.shared::cta.b64 _, [%0], %1;" ::"r"(bar), "r"(bytes) : "memory"); }
__device__ __forceinline__ void mbar_arrive(uint32_t bar) { asm volatile("mbarrier.arrive.shared::cta.b64 _, [%0];" ::"r"(bar) : "memory"); }
__device__ __forceinline__ void mbar_arrive_cta(uint32_t bar, uint32_t cta) {
    asm volatile("{ .reg .b32 ra; mapa.shared::cluster.u32 ra, %0, %1; mbarrier.arrive.shared::cluster.b64 _, [ra]; }" ::"r"(bar), "r"(cta) : "memory");
}
__device__ __forceinline__ bool mbar_try(uint32_t bar, uint32_t parity) {
    uint32_t ok;
    asm volatile("{ .reg .pred p; mbarrier.try_wait.parity.shared::cta.b64 p, [%1], %2; selp.u32 %0, 1, 0, p; }" : "=r"(ok) : "r"(bar), "r"(parity) : "memory");
    return ok;
}
__device__ __forceinline__ void spin_guard(uint32_t& n) {
    asm volatile("{ .reg .pred p; add.u32 %0, %0, 1; setp.gt.u32 p, %0, 4194304; @p exit; }" : "+r"(n));
}
__device__ __forceinline__ void mbar_wait(uint32_t bar, uint32_t parity) {
    uint32_t n = 0;
    while (!mbar_try(bar, parity)) spin_guard(n);
}
__device__ __forceinline__ bool elect_one() {
    uint32_t pred;
    asm volatile("{ .reg .pred p; elect.sync _|p, 0xffffffff; selp.u32 %0, 1, 0, p; }" : "=r"(pred));
    return pred;
}
__device__ __forceinline__ void tma_ld2(uint32_t dst, const CUtensorMap* m, int c0, int c1, uint32_t bar) {
    asm volatile("cp.async.bulk.tensor.2d.shared::cluster.global.mbarrier::complete_tx::bytes [%0], [%1, {%3, %4}], [%2];"
                 ::"r"(dst), "l"(m), "r"(bar), "r"(c0), "r"(c1) : "memory");
}
__device__ __forceinline__ void tma_ld2_mc(uint32_t dst, const CUtensorMap* m, int c0, int c1, uint32_t bar) {
    asm volatile("cp.async.bulk.tensor.2d.shared::cluster.global.mbarrier::complete_tx::bytes.multicast::cluster [%0], [%1, {%3, %4}], [%2], %5;"
                 ::"r"(dst), "l"(m), "r"(bar), "r"(c0), "r"(c1), "h"((uint16_t)3) : "memory");
}
__device__ __forceinline__ void tma_ld3(uint32_t dst, const CUtensorMap* m, int c0, int c1, int c2, uint32_t bar) {
    asm volatile("cp.async.bulk.tensor.3d.shared::cluster.global.mbarrier::complete_tx::bytes [%0], [%1, {%3, %4, %5}], [%2];"
                 ::"r"(dst), "l"(m), "r"(bar), "r"(c0), "r"(c1), "r"(c2) : "memory");
}
__device__ __forceinline__ void tma_st2(const CUtensorMap* m, uint32_t src, int c0, int c1) {
    asm volatile("cp.async.bulk.tensor.2d.global.shared::cta.bulk_group [%0, {%2, %3}], [%1];" ::"l"(m), "r"(src), "r"(c0), "r"(c1) : "memory");
}
__device__ __forceinline__ void tma_red2(const CUtensorMap* m, uint32_t src, int c0, int c1) {
    asm volatile("cp.reduce.async.bulk.tensor.2d.global.shared::cta.add.bulk_group [%0, {%2, %3}], [%1];" ::"l"(m), "r"(src), "r"(c0), "r"(c1) : "memory");
}
__device__ __forceinline__ void tma_red3(const CUtensorMap* m, uint32_t src, int c0, int c1, int c2) {
    asm volatile("cp.reduce.async.bulk.tensor.3d.global.shared::cta.add.bulk_group [%0, {%2, %3, %4}], [%1];" ::"l"(m), "r"(src), "r"(c0), "r"(c1), "r"(c2) : "memory");
}
__device__ __forceinline__ void bulk_commit() { asm volatile("cp.async.bulk.commit_group;" ::: "memory"); }
template <int N> __device__ __forceinline__ void bulk_wait_read() { asm volatile("cp.async.bulk.wait_group.read %0;" ::"n"(N) : "memory"); }
template <int N> __device__ __forceinline__ void bulk_wait() { asm volatile("cp.async.bulk.wait_group %0;" ::"n"(N) : "memory"); }
__device__ __forceinline__ void l2_prefetch(const void* p, uint32_t bytes) { asm volatile("cp.async.bulk.prefetch.L2.global [%0], %1;" ::"l"(p), "r"(bytes) : "memory"); }
__device__ __forceinline__ void fence_async_smem() { asm volatile("fence.proxy.async.shared::cta;" ::: "memory"); }
__device__ __forceinline__ void fence_async_all() { asm volatile("fence.proxy.async;" ::: "memory"); }
__device__ __forceinline__ void fence_gpu() { asm volatile("fence.acq_rel.gpu;" ::: "memory"); }
__device__ __forceinline__ void cluster_arrive() { asm volatile("barrier.cluster.arrive.aligned;" ::: "memory"); }
__device__ __forceinline__ void cluster_wait() { asm volatile("barrier.cluster.wait.aligned;" ::: "memory"); }
__device__ __forceinline__ unsigned ld_acq(const unsigned* p) { unsigned v; asm volatile("ld.acquire.gpu.global.u32 %0, [%1];" : "=r"(v) : "l"(p) : "memory"); return v; }
__device__ __forceinline__ void red_rel(unsigned* p, unsigned v) { asm volatile("red.release.gpu.global.add.u32 [%0], %1;" ::"l"(p), "r"(v) : "memory"); }
__device__ __forceinline__ void red_rlx(unsigned* p, unsigned v) { asm volatile("red.relaxed.gpu.global.add.u32 [%0], %1;" ::"l"(p), "r"(v) : "memory"); }
__device__ __forceinline__ void poll_flag(int idx, unsigned tgt) {
    const unsigned* f = &g_flags[idx * 8];
    uint32_t n = 0;
    while ((int)(ld_acq(f) - tgt) < 0) spin_guard(n);
}
__device__ __forceinline__ void wg_fence() { asm volatile("wgmma.fence.sync.aligned;" ::: "memory"); }
__device__ __forceinline__ void wg_commit() { asm volatile("wgmma.commit_group.sync.aligned;" ::: "memory"); }
template <int N> __device__ __forceinline__ void wg_wait() { asm volatile("wgmma.wait_group.sync.aligned %0;" ::"n"(N) : "memory"); }
template <int N> __device__ __forceinline__ void reg_fence(float (&d)[N]) {
#pragma unroll
    for (int i = 0; i < N; i++) asm volatile("" : "+f"(d[i])::"memory");
}
__device__ __forceinline__ uint32_t pack2(float lo, float hi) { uint32_t r; asm("cvt.rn.bf16x2.f32 %0, %1, %2;" : "=r"(r) : "f"(hi), "f"(lo)); return r; }
__device__ __forceinline__ void stsm4(uint32_t a, uint32_t r0, uint32_t r1, uint32_t r2, uint32_t r3) {
    asm volatile("stmatrix.sync.aligned.m8n8.x4.shared.b16 [%0], {%1,%2,%3,%4};" ::"r"(a), "r"(r0), "r"(r1), "r"(r2), "r"(r3) : "memory");
}
__device__ __forceinline__ void stsm4t(uint32_t a, uint32_t r0, uint32_t r1, uint32_t r2, uint32_t r3) {
    asm volatile("stmatrix.sync.aligned.m8n8.x4.trans.shared.b16 [%0], {%1,%2,%3,%4};" ::"r"(a), "r"(r0), "r"(r1), "r"(r2), "r"(r3) : "memory");
}
__device__ __forceinline__ float2 lds2(uint32_t a) { float2 v; asm volatile("ld.shared.v2.f32 {%0,%1}, [%2];" : "=f"(v.x), "=f"(v.y) : "r"(a) : "memory"); return v; }
__device__ __forceinline__ void sts2(uint32_t a, float2 v) { asm volatile("st.shared.v2.f32 [%0], {%1,%2};" ::"r"(a), "f"(v.x), "f"(v.y) : "memory"); }
__device__ __forceinline__ float bf_lo(uint32_t v) { return __uint_as_float(v << 16); }
__device__ __forceinline__ float bf_hi(uint32_t v) { return __uint_as_float(v & 0xffff0000u); }
__device__ __forceinline__ float warp_sum(float v) {
#pragma unroll
    for (int o = 16; o; o >>= 1) v += __shfl_xor_sync(0xffffffffu, v, o);
    return v;
}
__device__ __forceinline__ float tanh_fast(float x) { float y; asm("tanh.approx.f32 %0, %1;" : "=f"(y) : "f"(x)); return y; }

constexpr uint64_t DESC_K = (1ull << 62) | (64ull << 32) | (1ull << 16);
constexpr uint64_t DESC_N = (1ull << 62) | (64ull << 32) | (512ull << 16);

template<int TB>
__device__ __forceinline__ void wgmma_n80(float (&d)[40], uint64_t da, uint64_t db, uint32_t scaleD) {
    asm volatile("{\n.reg .pred p;\nsetp.ne.b32 p, %42, 0;\n"
    "wgmma.mma_async.sync.aligned.m64n80k16.f32.bf16.bf16 {%0, %1, %2, %3, %4, %5, %6, %7, %8, %9, %10, %11, %12, %13, %14, %15, %16, %17, %18, %19, %20, %21, %22, %23, %24, %25, %26, %27, %28, %29, %30, %31, %32, %33, %34, %35, %36, %37, %38, %39}, %40, %41, p, 1, 1, 0, %43;\n}\n"
    : "+f"(d[0]), "+f"(d[1]), "+f"(d[2]), "+f"(d[3]), "+f"(d[4]), "+f"(d[5]), "+f"(d[6]), "+f"(d[7]), "+f"(d[8]), "+f"(d[9]), "+f"(d[10]), "+f"(d[11]), "+f"(d[12]), "+f"(d[13]), "+f"(d[14]), "+f"(d[15]), "+f"(d[16]), "+f"(d[17]), "+f"(d[18]), "+f"(d[19]), "+f"(d[20]), "+f"(d[21]), "+f"(d[22]), "+f"(d[23]), "+f"(d[24]), "+f"(d[25]), "+f"(d[26]), "+f"(d[27]), "+f"(d[28]), "+f"(d[29]), "+f"(d[30]), "+f"(d[31]), "+f"(d[32]), "+f"(d[33]), "+f"(d[34]), "+f"(d[35]), "+f"(d[36]), "+f"(d[37]), "+f"(d[38]), "+f"(d[39])
    : "l"(da), "l"(db), "r"(scaleD), "n"(TB));
}

template<int TB>
__device__ __forceinline__ void wgmma_n128(float (&d)[64], uint64_t da, uint64_t db, uint32_t scaleD) {
    asm volatile("{\n.reg .pred p;\nsetp.ne.b32 p, %66, 0;\n"
    "wgmma.mma_async.sync.aligned.m64n128k16.f32.bf16.bf16 {%0, %1, %2, %3, %4, %5, %6, %7, %8, %9, %10, %11, %12, %13, %14, %15, %16, %17, %18, %19, %20, %21, %22, %23, %24, %25, %26, %27, %28, %29, %30, %31, %32, %33, %34, %35, %36, %37, %38, %39, %40, %41, %42, %43, %44, %45, %46, %47, %48, %49, %50, %51, %52, %53, %54, %55, %56, %57, %58, %59, %60, %61, %62, %63}, %64, %65, p, 1, 1, 0, %67;\n}\n"
    : "+f"(d[0]), "+f"(d[1]), "+f"(d[2]), "+f"(d[3]), "+f"(d[4]), "+f"(d[5]), "+f"(d[6]), "+f"(d[7]), "+f"(d[8]), "+f"(d[9]), "+f"(d[10]), "+f"(d[11]), "+f"(d[12]), "+f"(d[13]), "+f"(d[14]), "+f"(d[15]), "+f"(d[16]), "+f"(d[17]), "+f"(d[18]), "+f"(d[19]), "+f"(d[20]), "+f"(d[21]), "+f"(d[22]), "+f"(d[23]), "+f"(d[24]), "+f"(d[25]), "+f"(d[26]), "+f"(d[27]), "+f"(d[28]), "+f"(d[29]), "+f"(d[30]), "+f"(d[31]), "+f"(d[32]), "+f"(d[33]), "+f"(d[34]), "+f"(d[35]), "+f"(d[36]), "+f"(d[37]), "+f"(d[38]), "+f"(d[39]), "+f"(d[40]), "+f"(d[41]), "+f"(d[42]), "+f"(d[43]), "+f"(d[44]), "+f"(d[45]), "+f"(d[46]), "+f"(d[47]), "+f"(d[48]), "+f"(d[49]), "+f"(d[50]), "+f"(d[51]), "+f"(d[52]), "+f"(d[53]), "+f"(d[54]), "+f"(d[55]), "+f"(d[56]), "+f"(d[57]), "+f"(d[58]), "+f"(d[59]), "+f"(d[60]), "+f"(d[61]), "+f"(d[62]), "+f"(d[63])
    : "l"(da), "l"(db), "r"(scaleD), "n"(TB));
}

template<int TB>
__device__ __forceinline__ void wgmma_n160(float (&d)[80], uint64_t da, uint64_t db, uint32_t scaleD) {
    asm volatile("{\n.reg .pred p;\nsetp.ne.b32 p, %82, 0;\n"
    "wgmma.mma_async.sync.aligned.m64n160k16.f32.bf16.bf16 {%0, %1, %2, %3, %4, %5, %6, %7, %8, %9, %10, %11, %12, %13, %14, %15, %16, %17, %18, %19, %20, %21, %22, %23, %24, %25, %26, %27, %28, %29, %30, %31, %32, %33, %34, %35, %36, %37, %38, %39, %40, %41, %42, %43, %44, %45, %46, %47, %48, %49, %50, %51, %52, %53, %54, %55, %56, %57, %58, %59, %60, %61, %62, %63, %64, %65, %66, %67, %68, %69, %70, %71, %72, %73, %74, %75, %76, %77, %78, %79}, %80, %81, p, 1, 1, 0, %83;\n}\n"
    : "+f"(d[0]), "+f"(d[1]), "+f"(d[2]), "+f"(d[3]), "+f"(d[4]), "+f"(d[5]), "+f"(d[6]), "+f"(d[7]), "+f"(d[8]), "+f"(d[9]), "+f"(d[10]), "+f"(d[11]), "+f"(d[12]), "+f"(d[13]), "+f"(d[14]), "+f"(d[15]), "+f"(d[16]), "+f"(d[17]), "+f"(d[18]), "+f"(d[19]), "+f"(d[20]), "+f"(d[21]), "+f"(d[22]), "+f"(d[23]), "+f"(d[24]), "+f"(d[25]), "+f"(d[26]), "+f"(d[27]), "+f"(d[28]), "+f"(d[29]), "+f"(d[30]), "+f"(d[31]), "+f"(d[32]), "+f"(d[33]), "+f"(d[34]), "+f"(d[35]), "+f"(d[36]), "+f"(d[37]), "+f"(d[38]), "+f"(d[39]), "+f"(d[40]), "+f"(d[41]), "+f"(d[42]), "+f"(d[43]), "+f"(d[44]), "+f"(d[45]), "+f"(d[46]), "+f"(d[47]), "+f"(d[48]), "+f"(d[49]), "+f"(d[50]), "+f"(d[51]), "+f"(d[52]), "+f"(d[53]), "+f"(d[54]), "+f"(d[55]), "+f"(d[56]), "+f"(d[57]), "+f"(d[58]), "+f"(d[59]), "+f"(d[60]), "+f"(d[61]), "+f"(d[62]), "+f"(d[63]), "+f"(d[64]), "+f"(d[65]), "+f"(d[66]), "+f"(d[67]), "+f"(d[68]), "+f"(d[69]), "+f"(d[70]), "+f"(d[71]), "+f"(d[72]), "+f"(d[73]), "+f"(d[74]), "+f"(d[75]), "+f"(d[76]), "+f"(d[77]), "+f"(d[78]), "+f"(d[79])
    : "l"(da), "l"(db), "r"(scaleD), "n"(TB));
}
template<int N, int TB> __device__ __forceinline__ void wgmma(float (&d)[N/2], uint64_t da, uint64_t db, uint32_t scaleD) {
    if constexpr (N == 80) wgmma_n80<TB>(d, da, db, scaleD);
    else if constexpr (N == 128) wgmma_n128<TB>(d, da, db, scaleD);
    else if constexpr (N == 160) wgmma_n160<TB>(d, da, db, scaleD);
}

#define TR(ev)
#define TRW(ev)

template <int N, int MT, int TB>
__device__ __forceinline__ void mma_half(float (&a0)[N / 2], float (&a1)[N / 2], uint64_t da, uint64_t db, uint32_t sc) {
    constexpr uint64_t BSTEP = TB ? 128 : 2;
    wgmma<N, TB>(a0, da, db, sc);
    if (MT == 2) wgmma<N, TB>(a1, da + 512, db, sc);
    wgmma<N, TB>(a0, da + 2, db + BSTEP, 1);
    if (MT == 2) wgmma<N, TB>(a1, da + 514, db + BSTEP, 1);
}
template <int N, int MT, int TB>
__device__ __forceinline__ void mma_tile(float (&a0)[N / 2], float (&a1)[N / 2], uint32_t sa, uint32_t sb, uint32_t sc) {
    constexpr uint64_t BSTEP = TB ? 128 : 2;
    uint64_t da = DESC_K | ((sa & 0x3FFFF) >> 4), db = (TB ? DESC_N : DESC_K) | ((sb & 0x3FFFF) >> 4);
    wg_fence();
    mma_half<N, MT, TB>(a0, a1, da, db, sc);
    mma_half<N, MT, TB>(a0, a1, da + 4, db + 2 * BSTEP, 1);
    wg_commit();
}

__device__ __forceinline__ float2 row_stats(const uint2 (&v)[5]) {
    float s = 0.f;
#pragma unroll
    for (int q = 0; q < 5; q++) s += (bf_lo(v[q].x) + bf_hi(v[q].x)) + (bf_lo(v[q].y) + bf_hi(v[q].y));
    float mean = warp_sum(s) * (1.f / D_);
    float m2 = 0.f;
#pragma unroll
    for (int q = 0; q < 5; q++) {
        float a = bf_lo(v[q].x) - mean, b = bf_hi(v[q].x) - mean, c = bf_lo(v[q].y) - mean, d = bf_hi(v[q].y) - mean;
        m2 += (a * a + b * b) + (c * c + d * d);
    }
    float var = warp_sum(m2) * (1.f / D_);
    float rstd = 1.0f / sqrtf(var + LN_EPS);
    return make_float2(rstd, -mean * rstd);
}

__device__ __forceinline__ bool s4_half(int p, int u) { return u == 1 ? (p >= 3) : (u == 3 ? (p < 3 || p >= 6) : false); }
__device__ __forceinline__ int s4_chunk(int p, int u, int rho) {
    if (u < 2) {
        int base = p < 3 ? 4 * p : 12 + 3 * (p - 3);
        return u == 0 ? base + rho : (p < 3 ? base + 2 + rho : base + 2);
    }
    if (u == 2) { int e = 2 * p + rho; return e < 12 ? (e >> 2) * 6 + (e & 3) : 11 + e; }
    if (p >= 3 && p < 6) return (p - 3) * 6 + 4 + rho;
    return p < 3 ? 18 + p : 15 + p;
}
__device__ __forceinline__ int s5_count(int b, int kq) { return b == 0 ? (kq < 2 ? 7 : (kq == 2 ? 6 : 8)) : (kq < 2 ? 6 : (kq == 2 ? 7 : 9)); }
__device__ __forceinline__ int s5_tile(int b, int kq, int t) {
    if (b == 0) return (kq == 0 ? 0 : kq == 1 ? 6 : kq == 2 ? 13 : 19) + t;
    return kq < 3 ? 6 * kq + t : 26 - t;
}
__device__ __forceinline__ int s5_mask(int b, int kq, int t) {
    if (b == 0) return (kq == 0 && t == 6) ? 1 : (kq == 1 && t == 0) ? 2 : 3;
    return (kq == 2 && t == 6) ? 1 : (kq == 3 && t == 8) ? 2 : 3;
}

struct Ctx {
    uint32_t sb;
    int lane, wq, wg;
};

__device__ __forceinline__ void piece_begin(uint32_t sb, int q) {
    if (q >= 2) mbar_wait(sb + B_ZEMPTY + (q & 1) * 8, ((q >> 1) - 1) & 1);
}
__device__ __forceinline__ void piece_end(uint32_t sb, int q, int lane) {
    fence_async_smem();
    __syncwarp();
    if (lane == 0) mbar_arrive(sb + B_ZFULL + (q & 1) * 8);
}

template <int N, int J0, int NJ>
__device__ __forceinline__ void stage_plain(const float (&a)[N / 2], uint32_t zrow, uint32_t sw) {
#pragma unroll
    for (int j = 0; j < NJ; j += 2) {
        const int J = J0 + j;
        stsm4(zrow + ((j << 4) ^ sw), pack2(a[4 * J], a[4 * J + 1]), pack2(a[4 * J + 2], a[4 * J + 3]),
              pack2(a[4 * J + 4], a[4 * J + 5]), pack2(a[4 * J + 6], a[4 * J + 7]));
    }
}
__device__ __forceinline__ void epi_reduce(const float (&a)[80], uint32_t sb, int& q, int lane, uint32_t rowoff, uint32_t sw) {
    piece_begin(sb, q); stage_plain<160, 0, 8>(a, sb + Z0 + (q & 1) * 8192 + rowoff, sw); piece_end(sb, q, lane); q++;
    piece_begin(sb, q); stage_plain<160, 8, 8>(a, sb + Z0 + (q & 1) * 8192 + rowoff, sw); piece_end(sb, q, lane); q++;
    piece_begin(sb, q); stage_plain<160, 16, 4>(a, sb + Z0 + (q & 1) * 8192 + rowoff, sw); piece_end(sb, q, lane); q++;
}
__device__ __forceinline__ float geglu(float g, float u) {
    float z = g * fmaf(g * g, 0.7978845608028654f * 0.044715f, 0.7978845608028654f);
    float hgu = 0.5f * g * u;
    return fmaf(hgu, tanh_fast(z), hgu);
}
__device__ __forceinline__ void epi_geglu(const float (&a)[64], const float2 (&cg)[8], const float2 (&cu)[8], float2 s0, float2 s1,
                                          uint32_t sb, int& q, int lane, uint32_t rowoff, uint32_t sw) {
    uint32_t r[16];
#pragma unroll
    for (int j = 0; j < 8; j++) {
        float g0 = fmaf(a[4 * j], s0.x, s0.y * cg[j].x), g1 = fmaf(a[4 * j + 1], s0.x, s0.y * cg[j].y);
        float g2 = fmaf(a[4 * j + 2], s1.x, s1.y * cg[j].x), g3 = fmaf(a[4 * j + 3], s1.x, s1.y * cg[j].y);
        float u0 = fmaf(a[32 + 4 * j], s0.x, s0.y * cu[j].x), u1 = fmaf(a[32 + 4 * j + 1], s0.x, s0.y * cu[j].y);
        float u2 = fmaf(a[32 + 4 * j + 2], s1.x, s1.y * cu[j].x), u3 = fmaf(a[32 + 4 * j + 3], s1.x, s1.y * cu[j].y);
        r[2 * j] = pack2(geglu(g0, u0), geglu(g1, u1));
        r[2 * j + 1] = pack2(geglu(g2, u2), geglu(g3, u3));
    }
    piece_begin(sb, q);
    uint32_t zrow = sb + Z0 + (q & 1) * 8192 + rowoff;
#pragma unroll
    for (int j = 0; j < 8; j += 2) stsm4(zrow + ((j << 4) ^ sw), r[2 * j], r[2 * j + 1], r[2 * j + 2], r[2 * j + 3]);
    piece_end(sb, q, lane);
    q++;
}

template <int MT>
__device__ __forceinline__ void s4_main(float (&a0)[64], float (&a1)[64], uint32_t sb, int u, int rb, uint32_t aoff, uint32_t ot_ord, int wq, int lane) {
    int n = u * 10, s = n % 3, ph = (n / 3) & 1;
    uint32_t prev = 0;
#pragma unroll 1
    for (int kt = 0; kt < 10; kt++) {
        mbar_wait(sb + B_FULLH + kt * 8, rb);
        mbar_wait(sb + B_FULLW + s * 8, ph);
        if (kt == 0) TRW(40 + u);
        mma_tile<128, MT, 1>(a0, a1, sb + hslot(kt) + aoff, sb + (7 + s) * SLOT, kt > 0);
        if (kt == 9 && wq == 0 && lane == 0) mbar_arrive(ot_ord);
        wg_wait<1>();
        if (kt > 0 && lane < 4) mbar_arrive_cta(prev, lane & 1);
        prev = sb + ((lane & 2) ? B_EMPTYW + s * 8 : B_EMPTYH + kt * 8);
        if (++s == 3) { s = 0; ph ^= 1; }
    }
    wg_wait<0>();
    reg_fence(a0);
    if (MT == 2) reg_fence(a1);
    if (lane < 4) mbar_arrive_cta(prev, lane & 1);
}

__global__ void __launch_bounds__(384, 1) fused_kernel(const __grid_constant__ Params P) {
    extern __shared__ __align__(1024) uint8_t smem_raw[];
    uint32_t sb = smem_u32(smem_raw);
    asm volatile("" : "+r"(sb));
    const int warp = __shfl_sync(0xffffffffu, threadIdx.x >> 5, 0);
    const int lane = threadIdx.x & 31;
    const int rho = blockIdx.x & 1;
    int ci, p;
    {
        int c = blockIdx.x >> 1, sg, mu;
        if (c < 4) { sg = 15; mu = c; }
        else if (c < 36) { sg = (c - 4) & 7; mu = (c - 4) >> 3; }
        else { sg = 8 + (c - 36) % 7; mu = (c - 36) / 7; }
        p = sg & 7; ci = (sg >> 3) * 4 + mu;
    }
    const int kq = p >> 1, nt = (p & 1) * 2 + rho;
    const unsigned ep1 = g_epoch[blockIdx.x] + 1;

    if (warp == 8) {
        if (lane == 0) {
            for (int s = 0; s < 5; s++) { mbar_init(sb + B_FULL + s * 8, 1); mbar_init(sb + B_EMPTY + s * 8, 8); mbar_init(sb + B_FULLB1 + s * 8, 1); }
            for (int s = 0; s < 10; s++) { mbar_init(sb + B_FULLH + s * 8, 1); mbar_init(sb + B_EMPTYH + s * 8, 16); }
            for (int s = 0; s < 3; s++) { mbar_init(sb + B_FULLW + s * 8, 1); mbar_init(sb + B_EMPTYW + s * 8, 8); }
            for (int s = 0; s < 4; s++) { mbar_init(sb + B_FULL5 + s * 8, 1); mbar_init(sb + B_EMPTY5 + s * 8, 8); }
            for (int s = 0; s < 2; s++) {
                mbar_init(sb + B_ORD + s * 8, 1); mbar_init(sb + B_EPI + s * 8, 4); mbar_init(sb + B_ZFULL + s * 8, 4);
                mbar_init(sb + B_ZEMPTY + s * 8, 1); mbar_init(sb + B_STAT + s * 8, 1);
            }
            asm volatile("fence.mbarrier_init.release.cluster;" ::: "memory");
        }
        __syncwarp();
    } else if (warp == 9) {
        if (lane < 16) asm volatile("prefetch.tensormap [%0];" ::"l"(reinterpret_cast<const CUtensorMap*>(&P) + lane) : "memory");
    }
    TRW(0);
    __syncthreads();
    cluster_arrive();

    if (warp >= 8) {
        asm volatile("setmaxnreg.dec.sync.aligned.u32 72;");
        if (warp == 8) {
            const int et = 2 * p + rho;
            const CUtensorMap* wdm = &P.wd_b[et >> 3];
            const int erow = (et & 7) * 80;
            if (elect_one()) {
                for (int j = 0; j < 5; j++) {
                    uint32_t bar = sb + B_FULLB1 + j * 8, dst = sb + ringB(j);
                    mbar_expect_tx(bar, 20480);
                    tma_ld2(dst, wdm, j * 128, erow, bar);
                    tma_ld2(dst + 10240, wdm, j * 128 + 64, erow, bar);
                }
            }
            __syncwarp();
            cluster_wait();
            int b = 0, ph = 0;
            for (int n = 0; n < 20; n++) {
                if (n >= 5) mbar_wait(sb + B_EMPTY + b * 8, ph ^ 1);
                int u = n >= 10, kt = n - 10 * u;
                if (elect_one()) {
                    uint32_t bar = sb + B_FULL + b * 8;
                    mbar_expect_tx(bar, 16384);
                    tma_ld2_mc(sb + ringA(b) + rho * 8192, &P.x_a, kt * 64, ci * 256 + u * 128 + rho * 64, bar);
                }
                __syncwarp();
                if (++b == 5) { b = 0; ph ^= 1; }
            }
            const int part = kq >> 1, sbase = (kq & 1) * 8;
            const CUtensorMap* wsm = &P.ws_a[part];
            uint32_t ready = 0;
            for (int n = 0; n < 32; n++) {
                int u = n >> 4, t = (n >> 1) & 7;
                int sblk = (t < 4 ? 2 * t : 2 * t - 7);
                int kcol = (sbase + sblk) * 128 + (n & 1) * 64;
                mbar_wait(sb + B_EMPTY + b * 8, ph ^ 1);
                uint32_t bar = sb + B_FULL + b * 8;
                if (elect_one()) {
                    mbar_expect_tx(bar, 36864);
                    tma_ld2_mc(sb + ringA(b) + rho * 8192, wsm, kcol, (2 * ci + u) * 128 + rho * 64, bar);
                }
                __syncwarp();
                if (!((ready >> sblk) & 1)) {
                    const unsigned* f = &g_flags[(FL_AB + (part * 4 + nt) * 16 + sbase + (lane & 7)) * 8];
                    uint32_t it = 0;
                    do {
                        ready = __ballot_sync(0xffffffffu, (int)(ld_acq(f) - ep1 * 2) >= 0);
                        spin_guard(it);
                    } while (!((ready >> sblk) & 1));
                    __syncwarp();
                    if (n == 0) TR(20);
                }
                if (elect_one()) tma_ld2(sb + ringB(b), &P.abt_ld, kcol, part * 640 + nt * 160, bar);
                __syncwarp();
                if (++b == 5) { b = 0; ph ^= 1; }
            }
            asm volatile("bar.arrive 1, 64;" ::: "memory");
            for (int u = 0; u < 2; u++) {
                poll_flag(FL_H + 2 * ci + u, ep1 * 16);
                TR(21 + u);
                for (int j = 0; j < 10; j++) {
                    if (u == 0) {
                        if (j == 1) mbar_wait(sb + B_EMPTY + 2 * 8, 1);
                        else if (j == 2) mbar_wait(sb + B_EMPTY + 3 * 8, 1);
                        else if (j == 3) mbar_wait(sb + B_EMPTY + 4 * 8, 1);
                        else if (j == 4) mbar_wait(sb + B_EMPTY + 0 * 8, 0);
                        else if (j == 7) mbar_wait(sb + B_EMPTY + 1 * 8, 0);
                    } else {
                        mbar_wait(sb + B_EMPTYH + j * 8, 0);
                    }
                    if (elect_one()) {
                        uint32_t bar = sb + B_FULLH + j * 8;
                        mbar_expect_tx(bar, 16384);
                        tma_ld2_mc(sb + hslot(j) + rho * 8192, &P.h_w, j * 64, (2 * ci + u) * 128 + rho * 64, bar);
                    }
                    __syncwarp();
                }
            }
            const int c0 = nt * 160 + (nt & 1) * 32, g2 = nt * 5 + ((nt & 1) ? 0 : 4);
            int n5 = 0;
            for (int u = 0; u < 2; u++) {
                const int cnt = s5_count(u, kq);
                uint32_t rdy = 0;
                for (int t = 0; t < cnt; t++, n5++) {
                    const int s = n5 & 3, kt = s5_tile(u, kq, t);
                    if (n5 < 4) mbar_wait(sb + B_EMPTYH + ((0x9742 >> (4 * n5)) & 15) * 8, 1);
                    else mbar_wait(sb + B_EMPTY5 + s * 8, ((n5 >> 2) - 1) & 1);
                    uint32_t bar = sb + B_FULL5 + s * 8;
                    if (elect_one()) {
                        uint32_t dst = sb + s * 24576;
                        mbar_expect_tx(bar, 40960);
                        tma_ld2(dst, &P.wdn_w, c0, kt * 64, bar);
                        tma_ld2(dst + 8192, &P.wdn_w, c0 + 64, kt * 64, bar);
                        tma_ld3(dst + 16384, &P.wdn_n, 0, kt * 64, g2, bar);
                    }
                    __syncwarp();
                    if (!((rdy >> kt) & 1)) {
                        const unsigned* f = &g_flags[(FL_ACT + (2 * ci + u) * 27 + (lane < 27 ? lane : 0)) * 8];
                        uint32_t it = 0;
                        do {
                            rdy = __ballot_sync(0xffffffffu, (int)(ld_acq(f) - ep1 * 2) >= 0);
                            spin_guard(it);
                        } while (!((rdy >> kt) & 1));
                        __syncwarp();
                    }
                    if (elect_one()) tma_ld2_mc(sb + a5slot(s) + rho * 8192, &P.act_m, kt * 64, (2 * ci + u) * 128 + rho * 64, bar);
                    __syncwarp();
                }
            }
            TR(23);
        } else if (warp == 9) {
            cluster_wait();
            {
                const __nv_bfloat16* ws = P.ws[kq >> 1] + (size_t)(ci * 256 + nt * 32 + lane) * S_ + (kq & 1) * 1024;
                mbar_wait(sb + B_FULLB1 + 4 * 8, 0);
                l2_prefetch(ws, 2048);
                mbar_wait(sb + B_EPI + 8, 0);
                l2_prefetch(ws + 128 * S_, 2048);
                if (lane < 27) l2_prefetch(reinterpret_cast<const char*>(P.wdn) + blockIdx.x * 17280 + lane * 640, 640);
            }
            asm volatile("bar.sync 1, 64;" ::: "memory");
            int s = 0, ph = 0;
            for (int u = 0; u < 4; u++) {
                const int col = s4_chunk(p, u, rho) * 64;
                const bool half = s4_half(p, u);
                for (int kt = 0; kt < 10; kt++) {
                    if (u == 0 && kt < 3) mbar_wait(sb + B_EMPTY + (2 + kt) * 8, 1);
                    else mbar_wait(sb + B_EMPTYW + s * 8, ph ^ 1);
                    if (elect_one()) {
                        uint32_t bar = sb + B_FULLW + s * 8, dst = sb + (7 + s) * SLOT;
                        mbar_expect_tx(bar, 16384);
                        if (half) {
                            tma_ld2_mc(dst + rho * 8192, rho ? &P.wu_b : &P.wg_b, col, kt * 64, bar);
                        } else {
                            tma_ld2(dst, &P.wg_b, col, kt * 64, bar);
                            tma_ld2(dst + 8192, &P.wu_b, col, kt * 64, bar);
                        }
                    }
                    __syncwarp();
                    if (++s == 3) { s = 0; ph ^= 1; }
                }
            }
        } else if (warp == 10) {
            cluster_wait();
            poll_flag(FL_S1 + ci, ep1 * 64);
            poll_flag(FL_RS + 2 * p + rho, ep1 * 32);
            {
                const float sg = (p >= 4) ? -1.f : 1.f;
                float2 v[8];
#pragma unroll
                for (int j = 0; j < 8; j++) v[j] = __ldcg(&g_stats1[ci * 256 + j * 32 + lane]);
                float2 r0 = __ldcg(reinterpret_cast<const float2*>(&g_rowsum[(2 * p + rho) * 80]) + lane);
                float2 r1 = make_float2(0.f, 0.f);
                if (lane < 8) r1 = __ldcg(reinterpret_cast<const float2*>(&g_rowsum[(2 * p + rho) * 80]) + 32 + lane);
#pragma unroll
                for (int j = 0; j < 8; j++) sts2(sb + SM_STATS + (j * 32 + lane) * 8, make_float2(v[j].x * sg, v[j].y * sg));
                sts2(sb + SM_RS + lane * 8, r0);
                if (lane < 8) sts2(sb + SM_RS + 256 + lane * 8, r1);
                __syncwarp();
                if (lane < 2) mbar_arrive(sb + B_STAT + lane * 8);
                TR(24);
            }
            for (int u = 0; u < 2; u++) {
                const int r = 2 * ci + u;
                poll_flag(FL_H + r, ep1 * 16);
                fence_async_all();
                for (int hb = 0; hb < 2; hb++) {
                    const int row0 = r * 128 + (2 * p + rho) * 8 + hb * 4;
                    uint2 v[4][5];
#pragma unroll
                    for (int a = 0; a < 4; a++)
#pragma unroll
                        for (int q = 0; q < 5; q++) v[a][q] = __ldcg(reinterpret_cast<const uint2*>(g_h + (size_t)(row0 + a) * D_) + q * 32 + lane);
#pragma unroll
                    for (int a = 0; a < 4; a++) {
#pragma unroll
                        for (int q = 0; q < 5; q++) reinterpret_cast<uint2*>(P.out + (size_t)(row0 + a) * D_)[q * 32 + lane] = v[a][q];
                        float2 st = row_stats(v[a]);
                        if (lane == 0) g_stats2[row0 + a] = st;
                    }
                }
                fence_async_all();
                __syncwarp();
                if (lane == 0) red_rel(&g_flags[(FL_S2 + r) * 8], 1);
                __syncwarp();
                poll_flag(FL_S2 + r, ep1 * 16);
                float2 v[4];
#pragma unroll
                for (int j = 0; j < 4; j++) v[j] = __ldcg(&g_stats2[r * 128 + j * 32 + lane]);
#pragma unroll
                for (int j = 0; j < 4; j++) sts2(sb + SM_STATS + u * 1024 + (j * 32 + lane) * 8, v[j]);
                __syncwarp();
                if (lane == 0) mbar_arrive(sb + B_STAT + u * 8);
                TR(25 + u);
            }
        } else {
            cluster_wait();
            if (lane == 0) {
                int q = 0;
                for (int un = 0; un < 10; un++) {
                    int np, flag, inc = 1;
                    if (un < 2) { np = 2; flag = FL_AB + p * 16 + 2 * ci + un; }
                    else if (un < 4) { np = 6; flag = FL_H + 2 * ci + (un - 2); }
                    else if (un < 8) { bool hf = s4_half(p, un - 4); np = hf ? 1 : 2; inc = np; flag = FL_ACT + (2 * ci + ((un - 4) >> 1)) * 27 + s4_chunk(p, un - 4, rho); }
                    else { np = 6; flag = -1; }
                    for (int k = 0; k < np; k++, q++) {
                        mbar_wait(sb + B_ZFULL + (q & 1) * 8, (q >> 1) & 1);
                        if (k == 0 && (un == 2 || un == 8)) fence_async_all();
                        uint32_t z = sb + Z0 + (q & 1) * 8192;
                        if (un < 2) {
                            tma_st2(&P.abt_st, sb + ((q & 1) ? ZS1_1 : ZS1_0), ci * 256 + un * 128 + k * 64, (2 * p + rho) * 80);
                        } else if (un < 4) {
                            int mb = k >= 3, pc = k - 3 * mb, row = (2 * ci + un - 2) * 128 + mb * 64;
                            if (pc < 2) tma_red2(&P.h_w, z, nt * 160 + pc * 64, row);
                            else tma_red3(&P.h_n, z, 0, row, nt * 5 + 4);
                        } else if (un < 8) {
                            int row = (2 * ci + ((un - 4) >> 1)) * 128 + (np == 1 ? rho : k) * 64;
                            tma_st2(&P.act_m, z, s4_chunk(p, un - 4, rho) * 64, row);
                        } else {
                            int mb = k >= 3, pc = k - 3 * mb, row = (2 * ci + un - 8) * 128 + mb * 64;
                            if (pc < 2) tma_red2(&P.out_w, z, nt * 160 + (nt & 1) * 32 + pc * 64, row);
                            else tma_red3(&P.out_n, z, 0, row, nt * 5 + ((nt & 1) ? 0 : 4));
                        }
                        bulk_commit();
                        if (k > 0) { bulk_wait_read<1>(); mbar_arrive(sb + B_ZEMPTY + ((q - 1) & 1) * 8); }
                    }
                    bulk_wait_read<0>();
                    mbar_arrive(sb + B_ZEMPTY + ((q - 1) & 1) * 8);
                    bulk_wait<0>();
                    if (flag >= 0) red_rel(&g_flags[flag * 8], inc);
                    TR(30 + un);
                }
            }
            __syncwarp();
        }
        cluster_arrive();
        cluster_wait();
    } else {
        asm volatile("setmaxnreg.inc.sync.aligned.u32 216;");
        const int wg = warp >> 2, wq = warp & 3;
        const uint32_t my_ord = sb + B_ORD + wg * 8, ot_ord = sb + B_ORD + (wg ^ 1) * 8;
        const uint32_t my_epi = sb + B_EPI + wg * 8, ot_epi = sb + B_EPI + (wg ^ 1) * 8;
        const uint32_t prow = wq * 16 + ((lane >> 3) & 1) * 8 + (lane & 7);
        const uint32_t rowoff = prow * 128, sw = (((lane >> 4) ^ (lane & 7)) << 4);
        const int srow = wq * 16 + (lane >> 2);

        if (wg == 1) {
            const int et = 2 * p + rho;
            const int row0 = ci * 256 + et * 16 + wq * 4;
            uint2 v[4][5], w[3][5];
#pragma unroll
            for (int a = 0; a < 4; a++)
#pragma unroll
                for (int q = 0; q < 5; q++) v[a][q] = __ldg(reinterpret_cast<const uint2*>(P.x + (size_t)(row0 + a) * D_) + q * 32 + lane);
            const __nv_bfloat16* wdp = P.wd[et >> 3] + (size_t)((et & 7) * 80 + ci * 10) * D_;
#pragma unroll
            for (int a = 0; a < 3; a++) {
                int t = min(wq + 4 * a, 9);
#pragma unroll
                for (int q = 0; q < 5; q++) w[a][q] = __ldg(reinterpret_cast<const uint2*>(wdp + (size_t)t * D_) + q * 32 + lane);
            }
#pragma unroll
            for (int a = 0; a < 4; a++) {
                float2 st = row_stats(v[a]);
                if (lane == 0) g_stats1[row0 + a] = st;
            }
#pragma unroll
            for (int a = 0; a < 3; a++) {
                float s = 0.f;
#pragma unroll
                for (int q = 0; q < 5; q++) s += (bf_lo(w[a][q].x) + bf_hi(w[a][q].x)) + (bf_lo(w[a][q].y) + bf_hi(w[a][q].y));
                s = warp_sum(s);
                if (lane == 0 && wq + 4 * a < 10) g_rowsum[et * 80 + ci * 10 + wq + 4 * a] = s;
            }
#pragma unroll
            for (int a = 0; a < 4; a++)
#pragma unroll
                for (int q = 0; q < 5; q++) reinterpret_cast<uint2*>(g_h + (size_t)(row0 + a) * D_)[q * 32 + lane] = v[a][q];
            fence_async_all();
            __syncwarp();
            if (lane == 0) {
                fence_gpu();
                red_rlx(&g_flags[(FL_S1 + ci) * 8], 1);
                red_rlx(&g_flags[(FL_RS + et) * 8], 1);
            }
            __syncwarp();
            TRW(1);
        }
        cluster_wait();

        int q;
        {
            float a0[40], a1[40];
            if (wg == 1) mbar_wait(my_ord, 0);
            int b = 0, ph = 0;
            uint32_t prev = 0;
#pragma unroll 1
            for (int kt = 0; kt < 10; kt++) {
                mbar_wait(sb + B_FULLB1 + (kt >> 1) * 8, 0);
                mbar_wait(sb + B_FULL + b * 8, ph);
                if (kt == 0) TRW(2 + wg);
                mma_tile<80, 2, 0>(a0, a1, sb + ringA(b), sb + ringB(kt >> 1) + (kt & 1) * 10240, kt > 0);
                if (kt == 9 && wq == 0 && lane == 0) mbar_arrive(ot_ord);
                wg_wait<1>();
                if (kt > 0 && lane < 2) mbar_arrive_cta(prev, lane);
                prev = sb + B_EMPTY + b * 8;
                if (++b == 5) { b = 0; ph ^= 1; }
            }
            wg_wait<0>();
            reg_fence(a0); reg_fence(a1);
            if (lane < 2) mbar_arrive_cta(prev, lane);
            TRW(4 + wg);
            mbar_wait(sb + B_STAT + wg * 8, 0);
            if (wg == 1) mbar_wait(ot_epi, 0);
            q = 2 * wg;
            const uint32_t trow = ((lane >> 4) * 8 + (lane & 7)) * 128, tsw = (((2 * wq + ((lane >> 3) & 1)) ^ (lane & 7)) << 4);
#pragma unroll
            for (int mb = 0; mb < 2; mb++) {
                const float(&a)[40] = mb ? a1 : a0;
                float2 s0 = lds2(sb + SM_STATS + wg * 1024 + (mb * 64 + srow) * 8), s1 = lds2(sb + SM_STATS + wg * 1024 + (mb * 64 + srow + 8) * 8);
                piece_begin(sb, q);
                uint32_t z = sb + (mb ? ZS1_1 : ZS1_0) + trow + tsw;
#pragma unroll
                for (int j = 0; j < 10; j += 2) {
                    float2 ra = lds2(sb + SM_RS + (8 * j + 2 * (lane & 3)) * 4), rb = lds2(sb + SM_RS + (8 * j + 8 + 2 * (lane & 3)) * 4);
                    stsm4t(z + j * 1024,
                           pack2(fmaf(a[4 * j], s0.x, s0.y * ra.x), fmaf(a[4 * j + 1], s0.x, s0.y * ra.y)),
                           pack2(fmaf(a[4 * j + 2], s1.x, s1.y * ra.x), fmaf(a[4 * j + 3], s1.x, s1.y * ra.y)),
                           pack2(fmaf(a[4 * j + 4], s0.x, s0.y * rb.x), fmaf(a[4 * j + 5], s0.x, s0.y * rb.y)),
                           pack2(fmaf(a[4 * j + 6], s1.x, s1.y * rb.x), fmaf(a[4 * j + 7], s1.x, s1.y * rb.y)));
                }
                piece_end(sb, q, lane);
                q++;
            }
            if (lane == 0) mbar_arrive(my_epi);
            TRW(6 + wg);
        }
        if (wg == 1 && wq < 2 && blockIdx.x * 2 + wq < 216) {
            const int task = blockIdx.x * 2 + wq;
            const __nv_bfloat16* wp = (task >= 108 ? P.wu : P.wg) + (size_t)(lane >> 1) * F_ + (task % 108) * 16 + (lane & 1) * 8;
            float s[8];
#pragma unroll
            for (int k = 0; k < 8; k++) s[k] = 0.f;
#pragma unroll 1
            for (int hb = 0; hb < 2; hb++) {
                uint4 v[20];
#pragma unroll
                for (int k = 0; k < 20; k++) v[k] = __ldg(reinterpret_cast<const uint4*>(wp + (size_t)(hb * 20 + k) * 16 * F_));
#pragma unroll
                for (int k = 0; k < 20; k++) {
                    s[0] += bf_lo(v[k].x); s[1] += bf_hi(v[k].x); s[2] += bf_lo(v[k].y); s[3] += bf_hi(v[k].y);
                    s[4] += bf_lo(v[k].z); s[5] += bf_hi(v[k].z); s[6] += bf_lo(v[k].w); s[7] += bf_hi(v[k].w);
                }
            }
#pragma unroll
            for (int k = 0; k < 8; k++)
#pragma unroll
                for (int o = 2; o < 32; o <<= 1) s[k] += __shfl_xor_sync(0xffffffffu, s[k], o);
            if (lane < 2) {
                float4* dst = reinterpret_cast<float4*>(&g_colsum[task * 16 + lane * 8]);
                dst[0] = make_float4(s[0], s[1], s[2], s[3]);
                dst[1] = make_float4(s[4], s[5], s[6], s[7]);
            }
            __syncwarp();
            if (lane == 0) red_rel(&g_flags[FL_CS * 8], 1);
            __syncwarp();
        }
        {
            float a0[80], a1[80];
            mbar_wait(my_ord, wg);
            int b = wg, ph = wg;
            uint32_t prev = 0;
#pragma unroll 1
            for (int kt = 0; kt < 16; kt++) {
                mbar_wait(sb + B_FULL + b * 8, ph);
                if (kt == 0) TRW(8 + wg);
                mma_tile<160, 2, 0>(a0, a1, sb + ringA(b), sb + ringB(b), kt > 0);
                if (kt == 15 && wq == 0 && lane == 0) mbar_arrive(ot_ord);
                wg_wait<1>();
                if (kt > 0 && lane < 2) mbar_arrive_cta(prev, lane);
                prev = sb + B_EMPTY + b * 8;
                if (++b == 5) { b = 0; ph ^= 1; }
            }
            wg_wait<0>();
            reg_fence(a0); reg_fence(a1);
            if (lane < 2) mbar_arrive_cta(prev, lane);
            TRW(10 + wg);
            mbar_wait(ot_epi, wg);
            q = 4 + 6 * wg;
            epi_reduce(a0, sb, q, lane, rowoff, sw);
            epi_reduce(a1, sb, q, lane, rowoff, sw);
            if (lane == 0) mbar_arrive(my_epi);
            TRW(12 + wg);
        }
        poll_flag(FL_CS, ep1 * 216);
        const int h1 = s4_half(p, 1), h3 = s4_half(p, 3);
#pragma unroll 1
        for (int rb = 0; rb < 2; rb++) {
            const int u = 2 * rb + wg;
            const bool half = wg && (rb ? h3 : h1);
            const int chunk = s4_chunk(p, u, rho);
            float2 cg[8], cu[8];
#pragma unroll
            for (int j = 0; j < 8; j++) {
                cg[j] = __ldcg(reinterpret_cast<const float2*>(&g_colsum[chunk * 64 + 8 * j + 2 * (lane & 3)]));
                cu[j] = __ldcg(reinterpret_cast<const float2*>(&g_colsum[F_ + chunk * 64 + 8 * j + 2 * (lane & 3)]));
            }
            float a0[64], a1[64];
            mbar_wait(my_ord, (wg + 1 + rb) & 1);
            if (half) s4_main<1>(a0, a1, sb, u, rb, rho * 8192, ot_ord, wq, lane);
            else s4_main<2>(a0, a1, sb, u, rb, 0, ot_ord, wq, lane);
            TRW(44 + u);
            mbar_wait(sb + B_STAT + rb * 8, 1);
            mbar_wait(ot_epi, (wg + 1 + rb) & 1);
            q = 16 + 2 * u - (u >= 2 ? h1 : 0);
            {
                const uint32_t st = sb + SM_STATS + rb * 1024 + ((half ? rho * 64 : 0) + srow) * 8;
                epi_geglu(a0, cg, cu, lds2(st), lds2(st + 64), sb, q, lane, rowoff, sw);
                if (!half) epi_geglu(a1, cg, cu, lds2(st + 512), lds2(st + 576), sb, q, lane, rowoff, sw);
            }
            if (lane == 0) mbar_arrive(my_epi);
            TRW(48 + u);
        }
        {
            float a0[80], a1[80];
            mbar_wait(my_ord, (wg + 3) & 1);
            const int cnt = s5_count(wg, kq);
            const int n0 = wg ? s5_count(0, kq) : 0;
            const int mfirst = s5_mask(wg, kq, 0), mlast = s5_mask(wg, kq, cnt - 1);
            const int hs0 = (mfirst == 2), hs1 = 2 * cnt - (mlast != 3);
            uint32_t prev = 0;
#pragma unroll 1
            for (int hs = hs0; hs < hs1; hs++) {
                const int n = n0 + (hs >> 1), s = n & 3;
                const int hi = (hs & 1) | ((hs == hs1 - 1) & (mlast == 2));
                mbar_wait(sb + B_FULL5 + s * 8, (n >> 2) & 1);
                if (hs == hs0) TRW(14 + wg);
                uint64_t da = DESC_K | (((sb + a5slot(s) + hi * 64) & 0x3FFFF) >> 4), db = DESC_N | (((sb + s * 24576 + hi * 4096) & 0x3FFFF) >> 4);
                wg_fence();
                mma_half<160, 2, 1>(a0, a1, da, db, hs > hs0);
                wg_commit();
                if (wg == 0 && hs == hs1 - 2 && wq == 0 && lane == 0) mbar_arrive(ot_ord);
                wg_wait<1>();
                if (prev && lane < 2) mbar_arrive_cta(prev, lane);
                prev = (hs & 1) ? sb + B_EMPTY5 + s * 8 : 0;
            }
            wg_wait<0>();
            reg_fence(a0); reg_fence(a1);
            if (lane < 2) mbar_arrive_cta(sb + B_EMPTY5 + ((n0 + cnt - 1) & 3) * 8, lane);
            TRW(16 + wg);
            mbar_wait(ot_epi, (wg + 3) & 1);
            q = 24 - h1 - h3 + 6 * wg;
            epi_reduce(a0, sb, q, lane, rowoff, sw);
            epi_reduce(a1, sb, q, lane, rowoff, sw);
            if (lane == 0) mbar_arrive(my_epi);
            TRW(18 + wg);
        }
        if (threadIdx.x == 0) g_epoch[blockIdx.x] = ep1;
        cluster_arrive();
        cluster_wait();
    }
}

typedef CUresult (*EncodeFn)(CUtensorMap*, CUtensorMapDataType, cuuint32_t, void*, const cuuint64_t*, const cuuint64_t*, const cuuint32_t*,
                             const cuuint32_t*, CUtensorMapInterleave, CUtensorMapSwizzle, CUtensorMapL2promotion, CUtensorMapFloatOOBfill);

void map2(EncodeFn enc, CUtensorMap* m, const void* ptr, uint64_t cols, uint64_t rows, uint32_t brows) {
    cuuint64_t gd[2] = {cols, rows}, gs[1] = {cols * 2};
    cuuint32_t bd[2] = {64, brows}, es[2] = {1, 1};
    enc(m, CU_TENSOR_MAP_DATA_TYPE_BFLOAT16, 2, const_cast<void*>(ptr), gd, gs, bd, es, CU_TENSOR_MAP_INTERLEAVE_NONE,
        CU_TENSOR_MAP_SWIZZLE_128B, CU_TENSOR_MAP_L2_PROMOTION_L2_256B, CU_TENSOR_MAP_FLOAT_OOB_FILL_NONE);
}
void map3n(EncodeFn enc, CUtensorMap* m, const void* ptr, uint64_t rows) {
    cuuint64_t gd[3] = {32, rows, 20}, gs[2] = {1280, 64};
    cuuint32_t bd[3] = {64, 64, 1}, es[3] = {1, 1, 1};
    enc(m, CU_TENSOR_MAP_DATA_TYPE_BFLOAT16, 3, const_cast<void*>(ptr), gd, gs, bd, es, CU_TENSOR_MAP_INTERLEAVE_NONE,
        CU_TENSOR_MAP_SWIZZLE_128B, CU_TENSOR_MAP_L2_PROMOTION_L2_256B, CU_TENSOR_MAP_FLOAT_OOB_FILL_NONE);
}

}

extern "C" void kernel_launch(void* const* d_in, const int* in_sizes, int n_in, void* d_out, int out_size) {
    static EncodeFn enc = nullptr;
    static void *abt, *h, *act;
    if (!enc) {
        void* fn = nullptr;
        cudaDriverEntryPointQueryResult st;
        cudaGetDriverEntryPoint("cuTensorMapEncodeTiled", &fn, cudaEnableDefault, &st);
        enc = (EncodeFn)fn;
        cudaGetSymbolAddress(&abt, g_abt);
        cudaGetSymbolAddress(&h, g_h);
        cudaGetSymbolAddress(&act, g_act);
        cudaFuncSetAttribute(fused_kernel, cudaFuncAttributeMaxDynamicSharedMemorySize, SMEM_BYTES);
    }
    Params P;
    typedef const __nv_bfloat16* BP;
    P.x = (BP)d_in[0]; P.ws[0] = (BP)d_in[1]; P.ws[1] = (BP)d_in[2]; P.wd[0] = (BP)d_in[3]; P.wd[1] = (BP)d_in[4];
    P.wg = (BP)d_in[6]; P.wu = (BP)d_in[7]; P.wdn = (BP)d_in[8]; P.out = (__nv_bfloat16*)d_out;
    map2(enc, &P.x_a, P.x, D_, S_, 64);
    map2(enc, &P.wd_b[0], P.wd[0], D_, D_, 80);
    map2(enc, &P.wd_b[1], P.wd[1], D_, D_, 80);
    map2(enc, &P.abt_st, abt, S_, 1280, 80);
    map2(enc, &P.abt_ld, abt, S_, 1280, 160);
    map2(enc, &P.ws_a[0], P.ws[0], S_, S_, 64);
    map2(enc, &P.ws_a[1], P.ws[1], S_, S_, 64);
    map2(enc, &P.h_w, h, D_, S_, 64);
    map3n(enc, &P.h_n, h, S_);
    map2(enc, &P.wg_b, P.wg, F_, D_, 64);
    map2(enc, &P.wu_b, P.wu, F_, D_, 64);
    map2(enc, &P.act_m, act, F_, S_, 64);
    map2(enc, &P.wdn_w, P.wdn, D_, F_, 64);
    map3n(enc, &P.wdn_n, P.wdn, F_);
    map2(enc, &P.out_w, d_out, D_, S_, 64);
    map3n(enc, &P.out_n, d_out, S_);

    cudaLaunchConfig_t cfg = {};
    cfg.gridDim = dim3(NCTA);
    cfg.blockDim = dim3(384);
    cfg.dynamicSmemBytes = SMEM_BYTES;
    cfg.stream = cudaStreamPerThread;
    cudaLaunchAttribute at[1];
    at[0].id = cudaLaunchAttributeClusterDimension;
    at[0].val.clusterDim.x = 2; at[0].val.clusterDim.y = 1; at[0].val.clusterDim.z = 1;
    cfg.attrs = at; cfg.numAttrs = 1;
    cudaLaunchKernelEx(&cfg, fused_kernel, P);
}
```

```cpp
#include <cuda_runtime.h>
#include <cuda_bf16.h>
#include <cuda.h>
#include <stdint.h>

#define TRACE 0

namespace {

constexpr int S_ = 2048, D_ = 640, F_ = 1728;
constexpr int NCTA = 132;
constexpr float LN_EPS = 1e-5f;
constexpr unsigned POLL_NS = 60, ACT_NS = 40, LAG_NS = 40, SUB_NS = 20;

__device__ __align__(1024) __nv_bfloat16 g_abt[1280 * 2048];
__device__ __align__(1024) __nv_bfloat16 g_act[S_ * F_];
constexpr int FL_AB = 0;
constexpr int FL_HI = FL_AB + 8 * 32;
constexpr int FL_H = FL_HI + 16 * 32;
constexpr int FL_CS = FL_H + 16 * 32;
constexpr int FL_ACT = FL_CS + 32;
constexpr int FL_N = FL_ACT + 16 * 32;
struct __align__(128) Small {
    unsigned epoch[160];
    uint16_t tab[3][128];
    unsigned flags[FL_N];
    unsigned long long place[64];
    unsigned long long rs[128 * 16];
    ulonglong2 st1[S_], st2[S_];
    float colsum[2 * F_];
};

struct Params {
    Small* sm;
    const __nv_bfloat16 *x, *wd[2];
    __nv_bfloat16* out;
    const __nv_bfloat16 *wg, *wu, *wdn;
    unsigned zero;
    CUtensorMap x_a, wd_b[2], abt_st, abt_ld, ws_a[2], h_w, h_n, h_l, wg_b, wu_b, act_m, wdn_w, wdn_n, h_sw, h_sn, act_s;
};
constexpr int NMAP = 18;

constexpr uint32_t ZS = 45 * 4096;
constexpr uint32_t ZB = 51 * 4096;
constexpr uint32_t SM_CT = 55 * 4096;
constexpr uint32_t SM_TAB = SM_CT + 2048;
constexpr uint32_t MISC = 56 * 4096;
constexpr uint32_t SM_STATS = MISC;
constexpr uint32_t SM_RS = MISC + 2048;
constexpr uint32_t SM_RDY = SM_RS + 320;
constexpr uint32_t BAR = SM_RDY + 32;
constexpr uint32_t B_FULL = BAR, B_EMPTY = B_FULL + 64, B_ORD = B_EMPTY + 64, B_ZFULL = B_ORD + 16, B_GATE = B_ZFULL + 48,
                   B_S1Z = B_GATE + 8, B_ST2 = B_S1Z + 8, B_ZEMPTY = B_ST2 + 16, B_ZP = B_ZEMPTY + 16, B_STAT = B_ZP + 16,
                   B_TAB = B_STAT + 16, B_HIZ = B_TAB + 8, B_FA = B_HIZ + 8, B_CS = B_FA + 16, B_DUMMY = B_CS + 8,
                   B_SIDE = B_DUMMY + 8, B_END = B_SIDE + 8;
__host__ __device__ constexpr uint32_t bar_count(uint32_t o) {
    return o < B_EMPTY ? 1 : o < B_ORD ? 8 : o < B_ZFULL ? 1 : o < B_S1Z ? 4 : o < B_ZEMPTY ? 2 : o == B_DUMMY ? 1000000 : 1;
}
constexpr uint32_t SMEM_BYTES = 232448;
static_assert(B_END <= SMEM_BYTES && B_ORD % 16 == 0, "smem");
__device__ Small g_small = {
    {1,1,1,1,1,1,1,1,1,1,1,1,1,1,1,1,1,1,1,1,1,1,1,1,1,1,1,1,1,1,1,1,1,1,1,1,1,1,1,1,1,1,1,1,1,1,1,1,1,1,1,1,1,1,1,1,1,1,1,1,1,1,1,1,1,1,1,1,1,1,1,1,1,1,1,1,1,1,1,1,1,1,1,1,1,1,1,1,1,1,1,1,1,1,1,1,1,1,1,1,1,1,1,1,1,1,1,1,1,1,1,1,1,1,1,1,1,1,1,1,1,1,1,1,1,1,1,1,1,1,1,1},
    {
    {49157,49742,50327,50912,51497,49157,49742,50327,52064,51484,49408,49769,50318,52055,50912,51456,18729,18126,19287,17568,16960,16681,50894,52069,51223,49728,49427,50894,51822,51237,49728,49430,50834,52110,51358,55722,53258,54662,54930,56206,55202,51584,17792,18082,19342,18322,18822,16394,21930,55450,56206,55186,55684,53760,55958,55450,56204,54302,53542,53256,55956,54818,21282,27540,25608,24870,24606,60060,54796,59534,54320,62766,57766,57374,54826,49954,50350,49574,16798,17578,13102,22050,16422,49566,50346,0,0,0,0,0,0,0,0,0,0,0},
    {49157,49742,50327,50912,51497,49157,49742,50327,52059,51172,51717,49161,50253,52054,50852,51141,18377,18061,19286,17508,16389,18953,50848,52054,50002,49157,51721,51108,50798,50132,49157,49770,51618,52122,50590,54414,53504,53802,55462,56218,55190,54414,20750,24598,25114,26790,27562,59276,54404,58246,54920,62848,56234,63906,53406,58002,53646,54682,56234,55462,55170,49546,17802,19330,18598,18346,16794,17806,21138,56192,55714,55966,53530,49814,50222,51456,51114,49434,16662,18350,14634,21504,17050,49430,51118,0,0,0,0,0,0,0,0,0,0,0},
    {49157,49742,50327,50912,51497,49157,49742,50327,52059,51172,51717,49161,50253,52054,50852,51141,18377,18061,19286,17508,16389,18953,50848,52054,50002,49157,51721,51108,50798,50132,49157,49770,51618,52122,50590,54414,53504,53802,55462,56218,55190,54414,20750,24598,25114,26790,27562,59276,54404,58246,54920,62848,56234,63906,53386,58526,53646,54934,56234,55462,53890,55186,21394,24962,26278,27562,26774,57984,55182,58512,54918,61576,55470,59926,53918,50202,49158,51374,51734,49822,50202,17414,17070,18966,18590,16410,50182,0,0,0,0,0,0,0,0,0}
    }
};

__device__ __forceinline__ uint32_t smem_u32(const void* p) { return (uint32_t)__cvta_generic_to_shared(p); }
__device__ __forceinline__ void mbar_init(uint32_t bar, uint32_t cnt) { asm volatile("mbarrier.init.shared::cta.b64 [%0], %1;" ::"r"(bar), "r"(cnt)); }
__device__ __forceinline__ void mbar_expect_tx(uint32_t bar, uint32_t bytes) { asm volatile("mbarrier.arrive.expect_tx.shared::cta.b64 _, [%0], %1;" ::"r"(bar), "r"(bytes) : "memory"); }
__device__ __forceinline__ void mbar_arrive(uint32_t bar) { asm volatile("mbarrier.arrive.shared::cta.b64 _, [%0];" ::"r"(bar) : "memory"); }
__device__ __forceinline__ uint32_t lds16(uint32_t a) { uint32_t v; asm volatile("ld.shared.u16 %0, [%1];" : "=r"(v) : "r"(a) : "memory"); return v; }
__device__ __forceinline__ __attribute__((unused)) uint32_t clk32() { uint32_t t; asm volatile("mov.u32 %0, %%clock;" : "=r"(t)); return t; }
template <int LIM>
__device__ __forceinline__ void spin_guard(uint32_t& n, uint32_t tag) {
    asm volatile("{ .reg .pred p; setp.gt.u32 p, %0, %1; @p exit; add.u32 %0, %0, 1; }" : "+r"(n) : "n"(LIM));
}
__device__ __forceinline__ void mbar_wait(uint32_t bar, uint32_t parity) {
    asm volatile("{\n.reg .pred p;\n.reg .b32 n;\nmov.u32 n, 0;\n"
                 "LW: mbarrier.try_wait.parity.shared::cta.b64 p, [%0], %1;\n@p bra.uni LD;\n"
                 "add.u32 n, n, 1;\nsetp.lt.u32 p, n, 300000;\n@p bra.uni LW;\nexit;\nLD:\n}" ::"r"(bar), "r"(parity) : "memory");
}
__device__ __forceinline__ uint32_t mapa(uint32_t a, uint32_t cta) { uint32_t r; asm("mapa.shared::cluster.u32 %0, %1, %2;" : "=r"(r) : "r"(a), "r"(cta)); return r; }
__device__ __forceinline__ void mbar_arrive_mapped(uint32_t ra) { asm volatile("mbarrier.arrive.shared::cluster.b64 _, [%0+64];" ::"r"(ra) : "memory"); }
__device__ __forceinline__ bool elect_one() {
    uint32_t pred;
    asm volatile("{ .reg .pred p; elect.sync _|p, 0xffffffff; selp.u32 %0, 1, 0, p; }" : "=r"(pred));
    return pred;
}
__device__ __forceinline__ void tma_ld2(uint32_t dst, const CUtensorMap* m, int c0, int c1, uint32_t bar) {
    asm volatile("cp.async.bulk.tensor.2d.shared::cluster.global.mbarrier::complete_tx::bytes [%0], [%1, {%3, %4}], [%2];"
                 ::"r"(dst), "l"(m), "r"(bar), "r"(c0), "r"(c1) : "memory");
}
__device__ __forceinline__ void tma_ld2_mc(uint32_t dst, const CUtensorMap* m, int c0, int c1, uint32_t bar) {
    asm volatile("cp.async.bulk.tensor.2d.shared::cluster.global.mbarrier::complete_tx::bytes.multicast::cluster [%0], [%1, {%3, %4}], [%2], %5;"
                 ::"r"(dst), "l"(m), "r"(bar), "r"(c0), "r"(c1), "h"((uint16_t)3) : "memory");
}
__device__ __forceinline__ void tma_ld3(uint32_t dst, const CUtensorMap* m, int c0, int c1, int c2, uint32_t bar) {
    asm volatile("cp.async.bulk.tensor.3d.shared::cluster.global.mbarrier::complete_tx::bytes [%0], [%1, {%3, %4, %5}], [%2];"
                 ::"r"(dst), "l"(m), "r"(bar), "r"(c0), "r"(c1), "r"(c2) : "memory");
}
__device__ __forceinline__ void tma_st2(const CUtensorMap* m, uint32_t src, int c0, int c1) {
    asm volatile("cp.async.bulk.tensor.2d.global.shared::cta.bulk_group [%0, {%2, %3}], [%1];" ::"l"(m), "r"(src), "r"(c0), "r"(c1) : "memory");
}
__device__ __forceinline__ void tma_red2(const CUtensorMap* m, uint32_t src, int c0, int c1) {
    asm volatile("cp.reduce.async.bulk.tensor.2d.global.shared::cta.add.bulk_group [%0, {%2, %3}], [%1];" ::"l"(m), "r"(src), "r"(c0), "r"(c1) : "memory");
}
__device__ __forceinline__ void bulk_commit() { asm volatile("cp.async.bulk.commit_group;" ::: "memory"); }
template <int N> __device__ __forceinline__ void bulk_wait_read() { asm volatile("cp.async.bulk.wait_group.read %0;" ::"n"(N) : "memory"); }
template <int N> __device__ __forceinline__ void bulk_wait() { asm volatile("cp.async.bulk.wait_group %0;" ::"n"(N) : "memory"); }
__device__ __forceinline__ void l2_prefetch(const void* p, uint32_t bytes) { asm volatile("cp.async.bulk.prefetch.L2.global [%0], %1;" ::"l"(p), "r"(bytes) : "memory"); }
__device__ __forceinline__ void fence_async_smem() { asm volatile("fence.proxy.async.shared::cta;" ::: "memory"); }
__device__ __forceinline__ void cluster_arrive() { asm volatile("barrier.cluster.arrive.relaxed.aligned;" ::: "memory"); }
__device__ __forceinline__ void cluster_wait() { asm volatile("barrier.cluster.wait.aligned;" ::: "memory"); }
__device__ __forceinline__ void fence_rel() { asm volatile("fence.acq_rel.gpu;" ::: "memory"); }
__device__ __forceinline__ void red_rlx(unsigned* p, unsigned v) { asm volatile("red.relaxed.gpu.global.add.u32 [%0], %1;" ::"l"(p), "r"(v) : "memory"); }
__device__ __forceinline__ unsigned ld_epoch(const unsigned* p) { unsigned v; asm volatile("ld.global.u32 %0, [%1];" : "=r"(v) : "l"(p) : "memory"); return v; }
__device__ __forceinline__ unsigned ld_rlx(const unsigned* p) { unsigned v; asm volatile("ld.relaxed.gpu.global.u32 %0, [%1];" : "=r"(v) : "l"(p) : "memory"); return v; }
__device__ __forceinline__ void fence_acq() { asm volatile("fence.acquire.gpu;" ::: "memory"); }
__device__ __forceinline__ void poll_flag(const unsigned* f, unsigned tgt) {
    uint32_t t0 = 0;
    while ((int)(ld_rlx(f) - tgt) < 0) { __nanosleep(POLL_NS); spin_guard<1000000>(t0, 0x1000000); }
    fence_acq();
}
__device__ __forceinline__ void wg_fence() { asm volatile("wgmma.fence.sync.aligned;" ::: "memory"); }
__device__ __forceinline__ void wg_commit() { asm volatile("wgmma.commit_group.sync.aligned;" ::: "memory"); }
template <int N> __device__ __forceinline__ void wg_wait() { asm volatile("wgmma.wait_group.sync.aligned %0;" ::"n"(N) : "memory"); }
template <int N> __device__ __forceinline__ void reg_fence(float (&d)[N]) {
#pragma unroll
    for (int i = 0; i < N; i++) asm volatile("" : "+f"(d[i])::"memory");
}
__device__ __forceinline__ uint32_t pack2(float lo, float hi) { uint32_t r; asm("cvt.rn.bf16x2.f32 %0, %1, %2;" : "=r"(r) : "f"(hi), "f"(lo)); return r; }
__device__ __forceinline__ void stsm4(uint32_t a, uint32_t r0, uint32_t r1, uint32_t r2, uint32_t r3) {
    asm volatile("stmatrix.sync.aligned.m8n8.x4.shared.b16 [%0], {%1,%2,%3,%4};" ::"r"(a), "r"(r0), "r"(r1), "r"(r2), "r"(r3) : "memory");
}
__device__ __forceinline__ void stsm4t(uint32_t a, uint32_t r0, uint32_t r1, uint32_t r2, uint32_t r3) {
    asm volatile("stmatrix.sync.aligned.m8n8.x4.trans.shared.b16 [%0], {%1,%2,%3,%4};" ::"r"(a), "r"(r0), "r"(r1), "r"(r2), "r"(r3) : "memory");
}
__device__ __forceinline__ float2 lds2(uint32_t a) { float2 v; asm volatile("ld.shared.v2.f32 {%0,%1}, [%2];" : "=f"(v.x), "=f"(v.y) : "r"(a) : "memory"); return v; }
__device__ __forceinline__ float bf_lo(uint32_t v) { return __uint_as_float(v << 16); }
__device__ __forceinline__ float bf_hi(uint32_t v) { return __uint_as_float(v & 0xffff0000u); }
__device__ __forceinline__ void sts2(uint32_t a, float x, float y) { asm volatile("st.shared.v2.f32 [%0], {%1,%2};" ::"r"(a), "f"(x), "f"(y) : "memory"); }
__device__ __forceinline__ void sts1(uint32_t a, float x) { asm volatile("st.shared.f32 [%0], %1;" ::"r"(a), "f"(x) : "memory"); }
__device__ __forceinline__ unsigned long long tagw(float v, unsigned tag) { return ((unsigned long long)tag << 32) | __float_as_uint(v); }
__device__ __forceinline__ void st_tag2(ulonglong2* p, float2 v, unsigned tag) {
    asm volatile("st.relaxed.gpu.global.v2.b64 [%0], {%1, %2};" ::"l"(p), "l"(tagw(v.x, tag)), "l"(tagw(v.y, tag)) : "memory");
}
__device__ __forceinline__ void st_tag1(unsigned long long* p, float v, unsigned tag) {
    asm volatile("st.relaxed.gpu.global.b64 [%0], %1;" ::"l"(p), "l"(tagw(v, tag)) : "memory");
}
__device__ __forceinline__ ulonglong2 ld_tag2(const ulonglong2* p) {
    ulonglong2 v; asm volatile("ld.relaxed.gpu.global.v2.b64 {%0, %1}, [%2];" : "=l"(v.x), "=l"(v.y) : "l"(p) : "memory"); return v;
}
__device__ __forceinline__ unsigned long long ld_tag1(const unsigned long long* p) {
    unsigned long long v; asm volatile("ld.relaxed.gpu.global.b64 %0, [%1];" : "=l"(v) : "l"(p) : "memory"); return v;
}
__device__ __forceinline__ bool mbar_test(uint32_t bar, uint32_t parity) {
    uint32_t ok;
    asm volatile("{ .reg .pred p; mbarrier.test_wait.parity.shared::cta.b64 p, [%1], %2; selp.u32 %0, 1, 0, p; }" : "=r"(ok) : "r"(bar), "r"(parity) : "memory");
    return ok;
}
__device__ __forceinline__ void bulk_ld(uint32_t dst, const void* src, uint32_t bytes, uint32_t bar) {
    asm volatile("cp.async.bulk.shared::cluster.global.mbarrier::complete_tx::bytes [%0], [%1], %2, [%3];" ::"r"(dst), "l"(src), "r"(bytes), "r"(bar) : "memory");
}
__device__ __forceinline__ void bulk_st(void* dst, uint32_t src, uint32_t bytes) {
    asm volatile("cp.async.bulk.global.shared::cta.bulk_group [%0], [%1], %2;" ::"l"(dst), "r"(src), "r"(bytes) : "memory");
}
__device__ __forceinline__ uint4 lds4(uint32_t a) { uint4 v; asm volatile("ld.shared.v4.u32 {%0,%1,%2,%3}, [%4];" : "=r"(v.x), "=r"(v.y), "=r"(v.z), "=r"(v.w) : "r"(a) : "memory"); return v; }
__device__ __forceinline__ uint32_t lds_acq(uint32_t a) { uint32_t v; asm volatile("ld.acquire.cta.shared.u32 %0, [%1];" : "=r"(v) : "r"(a) : "memory"); return v; }
__device__ __forceinline__ void sts_rel(uint32_t a, uint32_t v) { asm volatile("st.release.cta.shared.u32 [%0], %1;" ::"r"(a), "r"(v) : "memory"); }
__device__ __forceinline__ void rdy_wait(uint32_t a, uint32_t need, uint32_t& have, uint32_t lag = 0) {
    if ((have & need) != need) {
        uint32_t t0 = 0;
        while (true) {
            have = lds_acq(a);
            if ((have & need) == need) { if (t0 && lag) __nanosleep(lag); break; }
            __nanosleep(32);
            spin_guard<1000000>(t0, 0x6000000 + (a & 15));
        }
    }
}
__device__ __forceinline__ void poll_mask(const unsigned* f, unsigned tgt, uint32_t all, uint32_t dst, int lane, uint32_t ns) {
    uint32_t t0 = 0, last = 0;
    while (last != all) {
        const uint32_t m = __ballot_sync(0xffffffffu, (int)(ld_rlx(f) - tgt) >= 0) & all;
        if (m == last) __nanosleep(ns);
        else {
            fence_acq();
            __syncwarp();
            if (lane == 0 && dst) sts_rel(dst, m);
            last = m;
        }
        spin_guard<1000000>(t0, 0x2000000 + (dst & 15));
    }
}
__device__ __forceinline__ void gather_stats(const ulonglong2* g, int hstride, uint32_t dst, const unsigned long long* rs, uint32_t rdst,
                                             bool with_rs, unsigned tag, int lane, uint32_t gate) {
    uint32_t t0 = 0;
    bool ok;
    do {
        if (t0) __nanosleep(100);
        else mbar_wait(gate, 0);
        ulonglong2 v[4];
        unsigned long long r[3];
        ok = true;
#pragma unroll
        for (int j = 0; j < 4; j++) v[j] = ld_tag2(g + (j >> 1) * hstride + (j & 1) * 32 + lane);
        if (with_rs) {
#pragma unroll
            for (int j = 0; j < 3; j++) { const int e = min(j * 32 + lane, 79); r[j] = ld_tag1(rs + e + (e / 10) * 6); }
#pragma unroll
            for (int j = 0; j < 3; j++) {
                ok = ok && (unsigned)(r[j] >> 32) == tag;
                sts1(rdst + min(j * 32 + lane, 79) * 4, __uint_as_float((unsigned)r[j]));
            }
        }
#pragma unroll
        for (int j = 0; j < 4; j++) {
            ok = ok && (unsigned)(v[j].x >> 32) == tag && (unsigned)(v[j].y >> 32) == tag;
            sts2(dst + (j * 32 + lane) * 8, __uint_as_float((unsigned)v[j].x), __uint_as_float((unsigned)v[j].y));
        }
        spin_guard<1000000>(t0, 0x3000000);
    } while (!__all_sync(0xffffffffu, ok));
}
__device__ __forceinline__ float tanh_fast(float x) { float y; asm("tanh.approx.f32 %0, %1;" : "=f"(y) : "f"(x)); return y; }

constexpr uint32_t DESC_K = 1u << 16, DESC_N = 512u << 16;
__device__ __forceinline__ void acc8(const uint4 v, float& s0, float& s1, float& q0, float& q1) {
    float a, b;
    a = bf_lo(v.x); b = bf_hi(v.x); s0 += a; s1 += b; q0 = fmaf(a, a, q0); q1 = fmaf(b, b, q1);
    a = bf_lo(v.y); b = bf_hi(v.y); s0 += a; s1 += b; q0 = fmaf(a, a, q0); q1 = fmaf(b, b, q1);
    a = bf_lo(v.z); b = bf_hi(v.z); s0 += a; s1 += b; q0 = fmaf(a, a, q0); q1 = fmaf(b, b, q1);
    a = bf_lo(v.w); b = bf_hi(v.w); s0 += a; s1 += b; q0 = fmaf(a, a, q0); q1 = fmaf(b, b, q1);
}
__device__ __forceinline__ float bf_round(float v) { return __bfloat162float(__float2bfloat16_rn(v)); }
__device__ __forceinline__ float2 ln_coef(float mean, float var) {
    float sd, r;
    asm("sqrt.approx.f32 %0, %1;" : "=f"(sd) : "f"(bf_round(bf_round(fmaxf(var, 0.f)) + LN_EPS)));
    asm("rcp.approx.f32 %0, %1;" : "=f"(r) : "f"(bf_round(sd)));
    return make_float2(r, -bf_round(mean));
}
__device__ __forceinline__ float2 fin_stats(float s, float q) {
#pragma unroll
    for (int o = 1; o < 8; o <<= 1) { s += __shfl_xor_sync(0xffffffffu, s, o); q += __shfl_xor_sync(0xffffffffu, q, o); }
    const float md = s * (1.f / D_);
    return ln_coef(md, fmaf(-md, md, q * (1.f / D_)));
}

__device__ __forceinline__ void hmma16(float (&d)[4], const uint4 a, uint32_t b) {
    asm volatile("mma.sync.aligned.m16n8k16.row.col.f32.bf16.bf16.f32 {%0,%1,%2,%3}, {%4,%5,%6,%7}, {%8,%8}, {%0,%1,%2,%3};"
                 : "+f"(d[0]), "+f"(d[1]), "+f"(d[2]), "+f"(d[3]) : "r"(a.x), "r"(a.y), "r"(a.z), "r"(a.w), "r"(b));
}
__device__ __forceinline__ void hmma8(float (&d)[4], uint32_t a0, uint32_t a1, uint32_t b) {
    asm volatile("mma.sync.aligned.m16n8k8.row.col.f32.bf16.bf16.f32 {%0,%1,%2,%3}, {%4,%5}, {%6}, {%0,%1,%2,%3};"
                 : "+f"(d[0]), "+f"(d[1]), "+f"(d[2]), "+f"(d[3]) : "r"(a0), "r"(a1), "r"(b));
}

template<int TB>
__device__ __forceinline__ void wgmma_n80(float (&d)[40], uint64_t da, uint64_t db, uint32_t scaleD) {
    asm volatile("{\n.reg .pred p;\nsetp.ne.b32 p, %42, 0;\n"
    "wgmma.mma_async.sync.aligned.m64n80k16.f32.bf16.bf16 {%0, %1, %2, %3, %4, %5, %6, %7, %8, %9, %10, %11, %12, %13, %14, %15, %16, %17, %18, %19, %20, %21, %22, %23, %24, %25, %26, %27, %28, %29, %30, %31, %32, %33, %34, %35, %36, %37, %38, %39}, %40, %41, p, 1, 1, 0, %43;\n}\n"
    : "+f"(d[0]), "+f"(d[1]), "+f"(d[2]), "+f"(d[3]), "+f"(d[4]), "+f"(d[5]), "+f"(d[6]), "+f"(d[7]), "+f"(d[8]), "+f"(d[9]), "+f"(d[10]), "+f"(d[11]), "+f"(d[12]), "+f"(d[13]), "+f"(d[14]), "+f"(d[15]), "+f"(d[16]), "+f"(d[17]), "+f"(d[18]), "+f"(d[19]), "+f"(d[20]), "+f"(d[21]), "+f"(d[22]), "+f"(d[23]), "+f"(d[24]), "+f"(d[25]), "+f"(d[26]), "+f"(d[27]), "+f"(d[28]), "+f"(d[29]), "+f"(d[30]), "+f"(d[31]), "+f"(d[32]), "+f"(d[33]), "+f"(d[34]), "+f"(d[35]), "+f"(d[36]), "+f"(d[37]), "+f"(d[38]), "+f"(d[39])
    : "l"(da), "l"(db), "r"(scaleD), "n"(TB));
}

template<int TB>
__device__ __forceinline__ void wgmma_n128(float (&d)[64], uint64_t da, uint64_t db, uint32_t scaleD) {
    asm volatile("{\n.reg .pred p;\nsetp.ne.b32 p, %66, 0;\n"
    "wgmma.mma_async.sync.aligned.m64n128k16.f32.bf16.bf16 {%0, %1, %2, %3, %4, %5, %6, %7, %8, %9, %10, %11, %12, %13, %14, %15, %16, %17, %18, %19, %20, %21, %22, %23, %24, %25, %26, %27, %28, %29, %30, %31, %32, %33, %34, %35, %36, %37, %38, %39, %40, %41, %42, %43, %44, %45, %46, %47, %48, %49, %50, %51, %52, %53, %54, %55, %56, %57, %58, %59, %60, %61, %62, %63}, %64, %65, p, 1, 1, 0, %67;\n}\n"
    : "+f"(d[0]), "+f"(d[1]), "+f"(d[2]), "+f"(d[3]), "+f"(d[4]), "+f"(d[5]), "+f"(d[6]), "+f"(d[7]), "+f"(d[8]), "+f"(d[9]), "+f"(d[10]), "+f"(d[11]), "+f"(d[12]), "+f"(d[13]), "+f"(d[14]), "+f"(d[15]), "+f"(d[16]), "+f"(d[17]), "+f"(d[18]), "+f"(d[19]), "+f"(d[20]), "+f"(d[21]), "+f"(d[22]), "+f"(d[23]), "+f"(d[24]), "+f"(d[25]), "+f"(d[26]), "+f"(d[27]), "+f"(d[28]), "+f"(d[29]), "+f"(d[30]), "+f"(d[31]), "+f"(d[32]), "+f"(d[33]), "+f"(d[34]), "+f"(d[35]), "+f"(d[36]), "+f"(d[37]), "+f"(d[38]), "+f"(d[39]), "+f"(d[40]), "+f"(d[41]), "+f"(d[42]), "+f"(d[43]), "+f"(d[44]), "+f"(d[45]), "+f"(d[46]), "+f"(d[47]), "+f"(d[48]), "+f"(d[49]), "+f"(d[50]), "+f"(d[51]), "+f"(d[52]), "+f"(d[53]), "+f"(d[54]), "+f"(d[55]), "+f"(d[56]), "+f"(d[57]), "+f"(d[58]), "+f"(d[59]), "+f"(d[60]), "+f"(d[61]), "+f"(d[62]), "+f"(d[63])
    : "l"(da), "l"(db), "r"(scaleD), "n"(TB));
}

template<int TB>
__device__ __forceinline__ void wgmma_n160(float (&d)[80], uint64_t da, uint64_t db, uint32_t scaleD) {
    asm volatile("{\n.reg .pred p;\nsetp.ne.b32 p, %82, 0;\n"
    "wgmma.mma_async.sync.aligned.m64n160k16.f32.bf16.bf16 {%0, %1, %2, %3, %4, %5, %6, %7, %8, %9, %10, %11, %12, %13, %14, %15, %16, %17, %18, %19, %20, %21, %22, %23, %24, %25, %26, %27, %28, %29, %30, %31, %32, %33, %34, %35, %36, %37, %38, %39, %40, %41, %42, %43, %44, %45, %46, %47, %48, %49, %50, %51, %52, %53, %54, %55, %56, %57, %58, %59, %60, %61, %62, %63, %64, %65, %66, %67, %68, %69, %70, %71, %72, %73, %74, %75, %76, %77, %78, %79}, %80, %81, p, 1, 1, 0, %83;\n}\n"
    : "+f"(d[0]), "+f"(d[1]), "+f"(d[2]), "+f"(d[3]), "+f"(d[4]), "+f"(d[5]), "+f"(d[6]), "+f"(d[7]), "+f"(d[8]), "+f"(d[9]), "+f"(d[10]), "+f"(d[11]), "+f"(d[12]), "+f"(d[13]), "+f"(d[14]), "+f"(d[15]), "+f"(d[16]), "+f"(d[17]), "+f"(d[18]), "+f"(d[19]), "+f"(d[20]), "+f"(d[21]), "+f"(d[22]), "+f"(d[23]), "+f"(d[24]), "+f"(d[25]), "+f"(d[26]), "+f"(d[27]), "+f"(d[28]), "+f"(d[29]), "+f"(d[30]), "+f"(d[31]), "+f"(d[32]), "+f"(d[33]), "+f"(d[34]), "+f"(d[35]), "+f"(d[36]), "+f"(d[37]), "+f"(d[38]), "+f"(d[39]), "+f"(d[40]), "+f"(d[41]), "+f"(d[42]), "+f"(d[43]), "+f"(d[44]), "+f"(d[45]), "+f"(d[46]), "+f"(d[47]), "+f"(d[48]), "+f"(d[49]), "+f"(d[50]), "+f"(d[51]), "+f"(d[52]), "+f"(d[53]), "+f"(d[54]), "+f"(d[55]), "+f"(d[56]), "+f"(d[57]), "+f"(d[58]), "+f"(d[59]), "+f"(d[60]), "+f"(d[61]), "+f"(d[62]), "+f"(d[63]), "+f"(d[64]), "+f"(d[65]), "+f"(d[66]), "+f"(d[67]), "+f"(d[68]), "+f"(d[69]), "+f"(d[70]), "+f"(d[71]), "+f"(d[72]), "+f"(d[73]), "+f"(d[74]), "+f"(d[75]), "+f"(d[76]), "+f"(d[77]), "+f"(d[78]), "+f"(d[79])
    : "l"(da), "l"(db), "r"(scaleD), "n"(TB));
}
template<int N, int TB> __device__ __forceinline__ void wgmma(float (&d)[N/2], uint64_t da, uint64_t db, uint32_t scaleD) {
    if constexpr (N == 80) wgmma_n80<TB>(d, da, db, scaleD);
    else if constexpr (N == 128) wgmma_n128<TB>(d, da, db, scaleD);
    else if constexpr (N == 160) wgmma_n160<TB>(d, da, db, scaleD);
}

#define TR(ev)
#define TRW(ev)
#define XT(k)
#define TS(k, n)

__device__ __forceinline__ uint64_t mkdesc(uint32_t lo) { uint64_t d; asm("mov.b64 %0, {%1, 0x40000040};" : "=l"(d) : "r"(lo)); return d; }
template <int V> __device__ __forceinline__ void dadd(uint64_t& d) { asm volatile("add.s64 %0, %0, %1;" : "+l"(d) : "n"(V)); }
template <int N, int MT, int TB, int KS>
__device__ __forceinline__ void mma_steps(float (&a0)[N / 2], float (&a1)[N / 2], uint32_t alo, uint32_t blo, bool sc) {
    constexpr int BSTEP = TB ? 128 : 2;
    uint64_t da = mkdesc(alo), db = mkdesc(blo);
#pragma unroll
    for (int k = 0; k < KS; k++) {
        wgmma<N, TB>(a0, da, db, k ? 1 : sc);
        if (MT == 2) { dadd<512>(da); wgmma<N, TB>(a1, da, db, k ? 1 : sc); }
        if (k + 1 < KS) { dadd<MT == 2 ? -510 : 2>(da); dadd<BSTEP>(db); }
    }
}
__device__ __forceinline__ bool s4_half(int p, int u) { return u == 1 ? (p >= 3) : (u == 3 ? (p < 3 || p >= 6) : false); }
__device__ __forceinline__ int s4_chunk(int p, int u, int rho) {
    if (u < 2) {
        if (p < 3) return 7 * p + (u ? 0 : 2) + rho;
        return (p < 6 ? 7 * (p - 3) + 4 : 3 * p + 3) + (u ? 2 : rho);
    }
    if (u == 2) { const int e = 2 * p + rho; return (e >> 2) * 7 + (e & 3); }
    if (p >= 3 && p < 6) return (p - 3) * 7 + 5 + rho;
    return p < 3 ? 7 * p + 4 : 19 + p;
}
__device__ __forceinline__ int s5_count(int b, int kq) { return b == 0 ? (kq < 3 ? 6 : 9) : (kq < 3 ? 7 : 6); }
__device__ __forceinline__ int s5_tile(int b, int kq, int t) {
    if (b == 0) return kq < 3 ? 7 * kq + 5 - t : (t < 3 ? 7 * t + 6 : 29 - t);
    return 7 * kq + t;
}

template <int N, int J0, int NJ, int C0>
__device__ __forceinline__ void stage_plain(const float (&a)[N / 2], uint32_t zrow, uint32_t sw) {
#pragma unroll
    for (int j = 0; j < NJ; j += 2) {
        const int J = J0 + j;
        stsm4(zrow + (((C0 + j) << 4) ^ sw), pack2(a[4 * J], a[4 * J + 1]), pack2(a[4 * J + 2], a[4 * J + 3]),
              pack2(a[4 * J + 4], a[4 * J + 5]), pack2(a[4 * J + 6], a[4 * J + 7]));
    }
}
__device__ __forceinline__ void z_acquire(uint32_t sb, int un) {
    if (un >= -1) mbar_wait(sb + B_ZEMPTY + ((un + 1) & 1) * 8, ((un + 1) >> 1) & 1);
}
__device__ __forceinline__ void z_publish(uint32_t zf, int g, int lane) {
    fence_async_smem();
    __syncwarp();
    if (lane == 0) mbar_arrive(zf + g * 8);
}
__device__ __forceinline__ uint32_t geglu2(float ag0, float ag1, float au0, float au1, float2 cg, float2 cu, float nm, float c0, float c1, float k,
                                           uint32_t& dep, uint32_t zero) {
    nm = __uint_as_float(__float_as_uint(nm) ^ (dep & zero));
    const float t0 = fmaf(nm, cg.x, ag0), t1 = fmaf(nm, cg.y, ag1), v0 = fmaf(nm, cu.x, au0), v1 = fmaf(nm, cu.y, au1);
    const float z0 = t0 * fmaf(t0 * t0, c1, c0), z1 = t1 * fmaf(t1 * t1, c1, c0);
    const float y0 = tanh_fast(z0), y1 = tanh_fast(z1);
    const uint32_t r = pack2((t0 * v0) * fmaf(y0, k, k), (t1 * v1) * fmaf(y1, k, k));
    dep = __float_as_uint(z1);
    return r;
}
__device__ __forceinline__ void epi_geglu(const float (&a)[64], const float2 (&cg)[8], const float2 (&cu)[8], float2 s0, float2 s1,
                                          uint32_t zrow, uint32_t sw, uint32_t zero) {
    constexpr float C = 0.7978845608028654f;
    const float k0 = 0.5f * s0.x * s0.x, k1 = 0.5f * s1.x * s1.x;
    const float c00 = C * s0.x, c01 = C * s1.x, c10 = (2.f * 0.044715f) * c00 * k0, c11 = (2.f * 0.044715f) * c01 * k1;
    uint32_t dep = 0;
#pragma unroll
    for (int j = 0; j < 8; j += 2) {
        const uint32_t r0 = geglu2(a[4 * j], a[4 * j + 1], a[32 + 4 * j], a[33 + 4 * j], cg[j], cu[j], s0.y, c00, c10, k0, dep, zero);
        const uint32_t r1 = geglu2(a[4 * j + 2], a[4 * j + 3], a[34 + 4 * j], a[35 + 4 * j], cg[j], cu[j], s1.y, c01, c11, k1, dep, zero);
        const uint32_t r2 = geglu2(a[4 * j + 4], a[4 * j + 5], a[36 + 4 * j], a[37 + 4 * j], cg[j + 1], cu[j + 1], s0.y, c00, c10, k0, dep, zero);
        const uint32_t r3 = geglu2(a[4 * j + 6], a[4 * j + 7], a[38 + 4 * j], a[39 + 4 * j], cg[j + 1], cu[j + 1], s1.y, c01, c11, k1, dep, zero);
        stsm4(zrow + ((j << 4) ^ sw), r0, r1, r2, r3);
    }
}

template <int N, int TB, bool K128 = false, bool OPEN = false>
__device__ __forceinline__ void mainloop(float (&a0)[N / 2], float (&a1)[N / 2], uint32_t tp, uint32_t tend, uint32_t& prev,
                                         uint32_t my_ord, int ord_par, bool t0, int lane, int trc, unsigned long long* trp) {
    const uint32_t ot_ord = my_ord ^ 8;
    bool sc = false;
    uint4 e = lds4(tp);
    if (ord_par >= 0) mbar_wait(my_ord, ord_par);
    mbar_wait(e.z, e.w);
    TRW(trc);
#pragma unroll 1
    while (true) {
        TS(2, n);
        const uint32_t cur = mapa(e.z, lane);
        wg_fence();
        if (K128) { mma_steps<N, 1, TB, 4>(a0, a0, e.x, e.y, sc); mma_steps<N, 1, TB, 4>(a0, a0, e.x + 512, e.y + 640, true); }
        else mma_steps<N, 2, TB, 4>(a0, a1, e.x, e.y, sc);
        wg_commit();
        sc = true;
        tp += 16;
        e = lds4(tp);
        const bool ok = mbar_test(e.z, e.w);
        wg_wait<1>();
        TS(3, n - 1);
        if (lane < 2) mbar_arrive_mapped(prev);
        prev = cur;
        if (tp == tend) break;
        if (!ok) mbar_wait(e.z, e.w);
    }
    if (OPEN) return;
    if (t0) mbar_arrive(ot_ord);
    wg_wait<0>();
    reg_fence(a0);
    if (!K128) reg_fence(a1);
    if (lane < 2) mbar_arrive_mapped(prev);
}
template <int TB>
__device__ __forceinline__ void tail160(float (&a0)[80], float (&a1)[80], uint32_t tp, uint32_t prev, uint32_t sb, int un, int j,
                                        uint32_t za, uint32_t zb, uint32_t zbar, uint32_t zpar, uint32_t my_ord, bool t0, int lane, uint32_t rowoff, uint32_t sw,
                                        int trc, unsigned long long* trp) {
    const bool paced = j < 3;
    const uint32_t zf = sb + B_ZFULL + (un & 1) * 16;
    const uint32_t zn = zb + (paced ? 0 : 16384) + (rowoff >> 1), swn = ((lane >> 4) ^ ((lane >> 1) & 3)) << 4;
    if (TB) {
    const uint4 e0 = lds4(tp), e1 = lds4(tp + 16), e2 = lds4(tp + 32);
    mbar_wait(e0.z, e0.w);
    wg_fence();
    mma_steps<160, 1, TB, 4>(a0, a0, e0.x, e0.y, true);
    wg_commit();
    mbar_wait(e1.z, e1.w);
    wg_wait<1>();
    if (lane < 2) mbar_arrive_mapped(prev);
    wg_fence();
    mma_steps<160, 1, TB, 4>(a0, a0, e1.x, e1.y, true);
    mbar_wait(e2.z, e2.w);
    wg_fence();
    mma_steps<160, 1, TB, 4>(a0, a0, e2.x, e2.y, true);
    wg_commit();
    wg_fence();
    mma_steps<160, 1, TB, 4>(a1, a1, e0.x + 512, e0.y, true);
    mma_steps<160, 1, TB, 4>(a1, a1, e1.x + 512, e1.y, true);
    wg_commit();
    mbar_wait(zbar, zpar);
    wg_wait<1>();
    reg_fence(a0);
    stage_plain<160, 0, 8, 0>(a0, zb + rowoff, sw);
    z_publish(zf, 0, lane);
    wg_fence();
    mma_steps<160, 1, TB, 4>(a1, a1, e2.x + 512, e2.y, true);
    wg_commit();
    if (t0) mbar_arrive(my_ord ^ 8);
    wg_wait<1>();
    if (lane < 4) mbar_arrive_mapped(mapa((lane & 2) ? e1.z : e0.z, lane & 1));
    stage_plain<160, 8, 8, 0>(a0, zb + 8192 + rowoff, sw);
    if (!paced) stage_plain<160, 16, 4, 0>(a0, zn, swn);
    z_publish(zf, 1, lane);
    wg_wait<0>();
    reg_fence(a1);
    if (lane < 2) mbar_arrive_mapped(mapa(e2.z, lane));
    TRW(trc);
    } else {
    if (t0) mbar_arrive(my_ord ^ 8);
    wg_wait<0>();
    reg_fence(a0);
    reg_fence(a1);
    if (lane < 2) mbar_arrive_mapped(prev);
    TRW(trc);
    mbar_wait(zbar, zpar);
    stage_plain<160, 0, 8, 0>(a0, zb + rowoff, sw);
    z_publish(zf, 0, lane);
    stage_plain<160, 0, 8, 0>(a1, zb + 8192 + rowoff, sw);
    z_publish(zf, 1, lane);
    }
    if (paced) mbar_wait(sb + B_ZP, 0);
    if (TB) stage_plain<160, 0, 8, 0>(a1, za + rowoff, sw);
    else stage_plain<160, 8, 8, 0>(a0, za + rowoff, sw);
    z_publish(zf, paced ? 0 : 2, lane);
    if (paced) mbar_wait(sb + B_ZP + 8, j & 1);
    stage_plain<160, 8, 8, 0>(a1, za + 8192 + rowoff, sw);
    if (paced) { z_publish(zf, 1, lane); mbar_wait(sb + B_ZP, 1); }
    if (paced) stage_plain<160, 16, 4, 0>(a0, zn, swn);
    stage_plain<160, 16, 4, 0>(a1, zn + 4096, swn);
    z_publish(zf, paced ? 0 : 3, lane);
}
__device__ __forceinline__ void mainloop_half(float (&a0)[64], uint32_t tp, uint32_t dummy, uint32_t my_ord, int ord_par, bool t0, int lane, int trc, unsigned long long* trp) {
    const uint32_t tend = tp + 160, ot_ord = my_ord ^ 8;
    uint4 e = lds4(tp);
    mbar_wait(my_ord, ord_par);
    uint32_t prev = dummy;
    bool sc = false;
    mbar_wait(e.z, e.w);
    TRW(trc);
#pragma unroll 1
    while (true) {
        TS(2, n);
        const uint4 f = lds4(tp + 16);
        wg_fence();
        mma_steps<128, 1, 1, 4>(a0, a0, e.x, e.y, sc);
        wg_commit();
        mbar_wait(f.z, f.w);
        TS(2, n + 1);
        const uint32_t cur = mapa(f.z, lane & 1);
        if (lane & 2) prev = mapa(e.z, lane & 1);
        wg_fence();
        mma_steps<128, 1, 1, 4>(a0, a0, f.x, f.y, true);
        wg_commit();
        sc = true;
        tp += 32;
        e = lds4(tp);
        const bool ok = mbar_test(e.z, e.w);
        if (tp == tend && t0) mbar_arrive(ot_ord);
        wg_wait<1>();
        TS(3, n - 1); TS(3, n - 2);
        if (lane < 4) mbar_arrive_mapped(prev);
        prev = cur;
        if (tp == tend) break;
        if (!ok) mbar_wait(e.z, e.w);
    }
    wg_wait<0>();
    reg_fence(a0);
    if (lane < 2) mbar_arrive_mapped(prev);
}

struct Role { int kq, nt, ci, ci2, nt2, q4, p4, sig, c4; };
__device__ __forceinline__ Role get_role(uint32_t sb, int rho) {
    mbar_wait(sb + B_TAB, 0);
    const int R = __shfl_sync(0xffffffffu, lds_acq(sb + SM_RDY + 4), 0), g = R >> 3, t = R & 7;
    Role o;
    o.kq = g >> 1;
    o.nt = (g & 1) * 2 + rho; o.ci = t;
    o.ci2 = (g & 1) * 4 + (t >> 1); o.nt2 = (t & 1) * 2 + rho;
    const int j = g < 4 ? g : (g & 1) * 2 + (t >> 2), s = g < 4 ? (t >> 2) * 2 : g < 6 ? 1 : 3;
    o.q4 = s * 4 + (t & 3); o.p4 = o.q4 >> 1; o.sig = o.q4 & 1; o.c4 = 2 * j + rho;
    return o;
}

__global__ void __cluster_dims__(2, 1, 1) __launch_bounds__(512, 1) fused_kernel(const __grid_constant__ Params P) {
    extern __shared__ __align__(1024) uint8_t smem_raw[];
    uint32_t sb = smem_u32(smem_raw);
    asm volatile("" : "+r"(sb));
    const int warp = __shfl_sync(0xffffffffu, threadIdx.x >> 5, 0);
    const int lane = threadIdx.x & 31;
    if (warp == 9) {
        if (blockIdx.x < 128 && elect_one()) {
            mbar_init(sb + B_SIDE, 1);
            asm volatile("fence.mbarrier_init.release.cluster;" ::: "memory");
            fence_async_smem();
            mbar_expect_tx(sb + B_SIDE, 20480 + 12800);
            bulk_ld(sb + ZS, P.wd[blockIdx.x >> 6] + (size_t)(blockIdx.x & 63) * 10 * D_, 12800, sb + B_SIDE);
            bulk_ld(sb + ZS + 20480, P.x + (size_t)blockIdx.x * 16 * D_, 20480, sb + B_SIDE);
        }
        __syncwarp();
        XT(3);
    } else if (warp == 10) {
        const uint32_t n = lane, a = (sb & 0x3FFFF) / 16 + (n % 5) * 2304 | DESC_K;
        asm volatile("st.shared.v4.u32 [%0], {%1,%2,%3,%4};" ::"r"(sb + SM_CT + n * 16), "r"(a), "r"(a + 1024),
                     "r"(sb + B_FULL + (n & 7) * 8), "r"((n >> 3) & 1) : "memory");
        if (lane < 8) asm volatile("st.shared.u32 [%0], %1;" ::"r"(sb + SM_RDY + lane * 4), "r"(0) : "memory");
        asm volatile("fence.release.sync_restrict::shared::cta.cluster;" ::: "memory");
        __syncwarp();
    } else if (warp == 8) {
        if (elect_one()) {
            asm volatile("prefetch.tensormap [%0];" ::"l"(&P.x_a) : "memory");
            asm volatile("prefetch.tensormap [%0];" ::"l"(&P.wd_b[0]) : "memory");
            asm volatile("prefetch.tensormap [%0];" ::"l"(&P.wd_b[1]) : "memory");
#pragma unroll
            for (uint32_t o = BAR; o < B_SIDE; o += 8) mbar_init(sb + o, bar_count(o));
            asm volatile("fence.mbarrier_init.release.cluster;" ::: "memory");
        }
        __syncwarp();
    }
    cluster_arrive();
    const int rho = blockIdx.x & 1;
    unsigned ep1 = ld_epoch(P.sm->epoch + blockIdx.x);
    int p, sb1;
    {
        const int c = blockIdx.x >> 1;
        int sg, mu;
        if (c < 4) { sg = 15; mu = c; }
        else if (c < 36) { sg = (c - 4) & 7; mu = (c - 4) >> 3; }
        else { sg = 8 + (c - 36) % 7; mu = ((c - 36) / 7) & 3; }
        p = sg & 7;
        sb1 = (sg >> 3) * 16 + mu;
    }
    const int et = 2 * p + rho;
    const bool helper = blockIdx.x >= 128;
    const uint32_t d0 = (sb & 0x3FFFF) >> 4;
    unsigned long long* trp = nullptr;
    TRW(0);

    if ((warp == 12 || warp == 13) && !helper) {
        const int w2 = warp - 12;
        cluster_wait();
        if (w2) __nanosleep(3000);
        gather_stats(&P.sm->st1[(sb1 + 8 * w2) * 64], 256, sb + SM_STATS + w2 * 1024, &P.sm->rs[et * 128], sb + SM_RS, w2 == 0, ep1, lane, sb + B_GATE);
        __syncwarp();
        if (lane == 0) mbar_arrive(sb + B_STAT + w2 * 8);
        TR(24 - w2);
    }
    if (helper) {
        cluster_wait();
        __nanosleep(2500);
        const __nv_bfloat16* wsrc = ((blockIdx.x & 2) ? P.wu : P.wg) + (size_t)rho * 320 * F_;
        const int tid = threadIdx.x;
        float s[8];
#pragma unroll
        for (int k = 0; k < 8; k++) s[k] = 0.f;
#pragma unroll 1
        for (int i = -2; i < 20; i++) {
            if (warp == 15 && i + 2 < 20) {
                if (elect_one()) {
                    const uint32_t bar = sb + B_FULL + ((i + 2) & 3) * 8;
                    mbar_expect_tx(bar, 55296);
                    bulk_ld(sb + ((i + 2) & 3) * 55296, wsrc + (size_t)(i + 2) * 16 * F_, 55296, bar);
                }
                __syncwarp();
            }
            if (i < 0) continue;
            mbar_wait(sb + B_FULL + (i & 3) * 8, (i >> 2) & 1);
            if (tid < 432) {
                const uint32_t a = sb + (i & 3) * 55296 + tid * 16;
                uint4 v[8];
#pragma unroll
                for (int r = 0; r < 8; r++) v[r] = lds4(a + r * 6912);
#pragma unroll
                for (int r = 0; r < 8; r++) {
                    s[0] += bf_lo(v[r].x); s[1] += bf_hi(v[r].x); s[2] += bf_lo(v[r].y); s[3] += bf_hi(v[r].y);
                    s[4] += bf_lo(v[r].z); s[5] += bf_hi(v[r].z); s[6] += bf_lo(v[r].w); s[7] += bf_hi(v[r].w);
                }
            }
            __syncthreads();
        }
        if (tid < 432) {
#pragma unroll
            for (int k = 0; k < 8; k += 2) sts2(sb + tid * 32 + k * 4, s[k], s[k + 1]);
        }
        asm volatile("barrier.cluster.arrive.aligned;\nbarrier.cluster.wait.aligned;" ::: "memory");
        if (tid < 432) {
            const uint32_t a = sb + (rho * 432 + tid) * 8;
            const float2 u0 = lds2(a), u1 = lds2(a + 6912);
            float2 u2, u3;
            asm volatile("ld.shared::cluster.v2.f32 {%0,%1}, [%4];\nld.shared::cluster.v2.f32 {%2,%3}, [%4+6912];"
                         : "=f"(u2.x), "=f"(u2.y), "=f"(u3.x), "=f"(u3.y) : "r"(mapa(a, rho ^ 1)) : "memory");
            reinterpret_cast<float2*>(P.sm->colsum + ((blockIdx.x >> 1) & 1) * F_)[rho * 432 + tid] =
                make_float2((u0.x + u1.x) + (u2.x + u3.x), (u0.y + u1.y) + (u2.y + u3.y));
        }
        asm volatile("barrier.cluster.arrive.aligned;\nbarrier.cluster.wait.aligned;" ::: "memory");
        if (warp == 1) {
            if (lane == 0) { fence_rel(); red_rlx(&P.sm->flags[FL_CS], 1); P.sm->epoch[blockIdx.x] = ep1 + 1; }
            TR(29);
        } else if (warp == 2) {
            if (elect_one()) {
#pragma unroll 1
                for (int k = 0; k < 27; k++) l2_prefetch(reinterpret_cast<const char*>(P.wdn) + ((blockIdx.x & 3) * 27 + k) * 20480, 20480);
            }
        }
        return;
    }
    if (warp == 8) {
        const CUtensorMap* wdm = &P.wd_b[et >> 3];
        if (elect_one()) {
            mbar_expect_tx(sb + B_FULL, 36864);
            tma_ld3(sb + 16384, wdm, 0, (et & 7) * 80, 0, sb + B_FULL);
        }
        __syncwarp();
        TR(62);
        cluster_wait();
        TR(27);
#pragma unroll 1
        for (int n = 0; n < 5; n++) {
            if (elect_one()) {
                const uint32_t st = sb + n * 36864, bar = sb + B_FULL + n * 8;
                tma_ld2_mc(st + rho * 8192, &P.x_a, n * 128 + rho * 64, sb1 * 64, bar);
                if (n < 4) {
                    mbar_expect_tx(bar + 8, 36864);
                    tma_ld3(st + 36864 + 16384, wdm, 0, (et & 7) * 80, 2 * n + 2, bar + 8);
                }
            }
            __syncwarp();
        }
        TR(63);
    }

    if (warp >= 12) {
        asm volatile("setmaxnreg.dec.sync.aligned.u32 56;");
        if (warp < 14) {
            const int w2 = warp - 12;
            const Role R = get_role(sb, rho);
            if (w2 == 0) {
                poll_mask(&P.sm->flags[FL_AB + ((R.kq >> 1) * 4 + R.nt2) * 32 + (R.kq & 1) * 16 + (lane & 15)], ep1 * 2, 0xffff, sb + SM_RDY, lane, 20);
            } else {
                __nanosleep(6000);
                poll_flag(&P.sm->flags[FL_CS], ep1 * 4);
                __syncwarp();
                if (lane == 0) mbar_arrive(sb + B_CS);
            }
#pragma unroll 1
            for (int job = 0; job < 2; job++) {
                const int r = 2 * R.c4 + job;
                poll_mask(&P.sm->flags[FL_H + r * 32 + (lane & 1)], ep1 * 16, 3, w2 ? 0 : sb + SM_RDY + 16 + job * 4, lane, POLL_NS);
                const int row = r * 128 + R.q4 * 8 + w2 * 4 + (lane >> 3);
                const uint4* src = reinterpret_cast<const uint4*>(P.out + (size_t)row * D_) + (lane & 7);
                uint4 v[10];
#pragma unroll
                for (int k = 0; k < 10; k++) v[k] = __ldcg(src + k * 8);
                float s0 = 0.f, s1 = 0.f, q0 = 0.f, q1 = 0.f;
#pragma unroll
                for (int k = 0; k < 10; k++) acc8(v[k], s0, s1, q0, q1);
                const float2 st = fin_stats(s0 + s1, q0 + q1);
                if ((lane & 7) == 0) st_tag2(P.sm->st2 + row, st, ep1);
                {
                    const ulonglong2* g = &P.sm->st2[r * 128 + w2 * 64 + lane];
                    uint32_t t0 = 0;
                    ulonglong2 g0, g1;
                    do {
                        g0 = ld_tag2(g); g1 = ld_tag2(g + 32);
                        spin_guard<1000000>(t0, 0x3000000);
                    } while (!__all_sync(0xffffffffu, (unsigned)(g0.x >> 32) == ep1 && (unsigned)(g0.y >> 32) == ep1 &&
                                                      (unsigned)(g1.x >> 32) == ep1 && (unsigned)(g1.y >> 32) == ep1));
                    const uint32_t d = sb + SM_STATS + job * 1024 + (w2 * 64 + lane) * 8;
                    sts2(d, __uint_as_float((unsigned)g0.x), __uint_as_float((unsigned)g0.y));
                    sts2(d + 256, __uint_as_float((unsigned)g1.x), __uint_as_float((unsigned)g1.y));
                    __syncwarp();
                    if (lane == 0) mbar_arrive(sb + B_ST2 + job * 8);
                    if (w2) TR(25 + job);
                }
            }
            poll_mask(&P.sm->flags[FL_ACT + (2 * R.ci + w2) * 32 + lane], ep1 * 2, 0x7ffffff, sb + SM_RDY + 8 + w2 * 4, lane, POLL_NS);
        } else {
            const int sw_ = 15 - warp;
            if (sw_ == 0 && elect_one()) {
#pragma unroll 1
                for (int k = 3; k < NMAP; k++) asm volatile("prefetch.tensormap [%0];" ::"l"(&P.x_a + k) : "memory");
            }
            __syncwarp();
            cluster_wait();
            if (sw_ == 1) {
                uint32_t ta[9];
#pragma unroll
                for (int k = 0; k < 9; k++) ta[k] = __ldg(&P.sm->tab[k / 3][(k % 3) * 32 + lane]);
                int rank;
                {
                    unsigned sm;
                    asm volatile("mov.u32 %0, %%smid;" : "=r"(sm));
                    const unsigned tp = sm >> 1;
                    const unsigned key = tp < 32 ? (tp & 7) * 16 + (tp >> 3) : tp < 60 ? (1 + (tp - 32) % 7) * 16 + 4 + (tp - 32) / 7
                                       : tp < 62 ? (tp - 54) * 16 + 8 : 4 + ((tp - 62) & 7);
                    if (rho == 0 && lane == 0) st_tag1(&P.sm->place[blockIdx.x >> 1], __uint_as_float(key * 64 + (blockIdx.x >> 1)), ep1);
                    unsigned long long k0, k1;
                    uint32_t t0 = 0;
                    __syncwarp();
                    __nanosleep(1500);
                    do {
                        __nanosleep(200);
                        k0 = ld_tag1(&P.sm->place[lane]); k1 = ld_tag1(&P.sm->place[32 + lane]);
                        spin_guard<1000000>(t0, 0x9000000);
                    } while (!__all_sync(0xffffffffu, (unsigned)(k0 >> 32) == ep1 && (unsigned)(k1 >> 32) == ep1));
                    const unsigned mine = __shfl_sync(0xffffffffu, (unsigned)((blockIdx.x & 64) ? k1 : k0), (blockIdx.x >> 1) & 31);
                    rank = __popc(__ballot_sync(0xffffffffu, (unsigned)k0 < mine)) + __popc(__ballot_sync(0xffffffffu, (unsigned)k1 < mine));
                }
                const int g = rank >> 3, q4 = (g < 4 ? ((rank >> 2) & 1) * 2 : g < 6 ? 1 : 3) * 4 + (rank & 3), p4 = q4 >> 1;
                if (lane == 0) asm volatile("st.shared.u32 [%0], %1;" ::"r"(sb + SM_RDY + 4), "r"(rank) : "memory");
                uint32_t tv[3];
#pragma unroll
                for (int k = 0; k < 3; k++) tv[k] = p4 < 3 ? ta[k] : p4 < 6 ? ta[3 + k] : ta[6 + k];
#pragma unroll 1
                for (int k = 0; k < 3; k++) {
                    const uint32_t e = k == 0 ? tv[0] : k == 1 ? tv[1] : tv[2], i = k * 32 + lane, n = 20 + i;
                    const uint32_t aoff = (n >= 52 && n < 92 && !(e >> 15) && s4_half(p4, (n - 52) / 10)) ? (q4 & 1) * 512 : 0;
                    asm volatile("st.shared.u16 [%0], %1;" ::"r"(sb + SM_TAB + i * 2), "h"((uint16_t)e) : "memory");
                    asm volatile("st.shared.v4.u32 [%0], {%1,%2,%3,%4};" ::"r"(sb + SM_CT + n * 16), "r"((d0 + (e & 63) * 256 + aoff) | DESC_K),
                                 "r"((d0 + ((e >> 6) & 63) * 256) | (n < 52 ? DESC_K : DESC_N)), "r"(sb + B_FULL + (n & 7) * 8), "r"((n >> 3) & 1) : "memory");
                }
                __syncwarp();
                if (lane == 0) mbar_arrive(sb + B_TAB);
                XT(0);
#pragma unroll 1
                for (int k = 0; k < 2; k++) {
                    if (elect_one())
                        asm volatile("cp.async.bulk.prefetch.tensor.2d.L2.global.tile [%0, {%1, %2}];" ::"l"(&P.ws_a[g >> 2]),
                                     "r"(((g >> 1) & 1) * 1024 + (2 * k + (rank & 1)) * 64), "r"(((g & 1) * 4 + ((rank & 7) >> 1)) * 256 + rho * 64) : "memory");
                    __syncwarp();
                    __nanosleep(200);
                }
            }
            const uint32_t z = sb + ZB;
            const uint32_t zf = sb + B_ZFULL + sw_ * 16;
            uint32_t f0 = 0, f1 = 0;
#pragma unroll 1
            for (int v = sw_; v < 4; v += 2) {
                mbar_wait(zf, f0); f0 ^= 1;
                if (elect_one()) {
#pragma unroll
                    for (int k = 0; k < 5; k++) {
                        int t = rho * 80 + k * 16 - (p & 1) * 32;
                        if (t < 0) t += 160;
                        tma_st2(&P.abt_st, sb + ZS + sw_ * 10240 + k * 2048, (sb1 + 4 * v) * 64, p * 160 + t);
                    }
                    bulk_commit();
                    bulk_wait<0>();
                    mbar_arrive(sb + B_ZEMPTY + sw_ * 8);
                    if (v >= 2) mbar_arrive(sb + B_S1Z);
                    fence_rel();
                    red_rlx(&P.sm->flags[FL_AB + p * 32 + sb1 + 4 * v], 1);
                }
                __syncwarp();
                if (v == 0 || v == 3) TR(30 + sw_);
            }
            if (sw_ == 1) {
                __nanosleep(500);
#pragma unroll 1
                for (int v = 0; v < 8; v++) {
                    if (elect_one()) bulk_st(P.out + (size_t)(blockIdx.x * 16 + v * 2) * D_, sb + ZS + 20480 + v * 2560, 2560);
                    __syncwarp();
                    __nanosleep(100);
                }
                if (elect_one()) {
                    bulk_commit();
                    bulk_wait<0>();
                    mbar_arrive(sb + B_HIZ);
                    fence_rel();
                    red_rlx(&P.sm->flags[FL_HI + (blockIdx.x >> 3) * 32], 1);
                }
                __syncwarp();
            }
            const Role R = get_role(sb, rho);
#pragma unroll 1
            for (int un = 2 + sw_; un < 10; un += 2) {
                const int r = (un >= 4 && un < 8) ? 2 * R.c4 + ((un - 4) >> 1) : 2 * (un < 4 ? R.ci2 : R.ci) + (un & 1);
                int flag, inc = 1;
                if (un == 3 || un == 4) {
                    mbar_wait(sb + B_FA + (sw_ ^ 1) * 8, 0);
                    if (elect_one()) { fence_rel(); red_rlx(&P.sm->flags[FL_H + (2 * R.ci2 + un - 3) * 32], 1); }
                    __syncwarp();
                    XT(10 + un);
                }
                if (un < 4) poll_flag(&P.sm->flags[FL_HI + r * 32], ep1 * 8);
                mbar_wait(zf, f0); f0 ^= 1;
                if (un >= 8) {
                    uint32_t have = 0;
                    rdy_wait(sb + SM_RDY + 8 + (un & 1) * 4, 0x7ffffff, have);
                }
                if (un >= 4 && un < 8) {
                    const bool hf = s4_half(R.p4, un - 4);
                    const int ch = s4_chunk(R.p4, un - 4, R.sig);
                    flag = FL_ACT + r * 32 + ch; inc = hf ? 1 : 2;
#pragma unroll 1
                    for (int j = 0; j < 8; j++) {
                        if (j == 4) { mbar_wait(zf + 8, f1); f1 ^= 1; if (hf) break; }
                        if (elect_one()) tma_st2(&P.act_s, z + j * 2048, ch * 64, r * 128 + (hf ? R.sig * 64 : 0) + j * 16);
                        __syncwarp();
                        __nanosleep(ACT_NS);
                    }
                } else {
                    const bool o = un >= 8;
                    const int ntx = o ? R.nt : R.nt2, c0 = ntx * 160 + rho * 32, g2 = ntx * 5 + (rho ? 0 : 4);
                    flag = o ? -1 : FL_H + r * 32 + 1;
                    if (un != 9) {
#pragma unroll 1
                        for (int k = 0; k < 5; k++) {
                            if (k & 1) { mbar_wait(zf + 8, f1); f1 ^= 1; }
                            else if (k) { mbar_wait(zf, f0); f0 ^= 1; }
#pragma unroll 1
                            for (int j = 0; j < 4; j++) {
                                if (elect_one()) {
                                    tma_red2(k < 4 ? &P.h_sw : &P.h_sn, z + (k & 1) * 8192 + j * 2048, k < 4 ? c0 + (o ? k & 1 : k >> 1) * 64 : g2 * 32,
                                             r * 128 + (k < 4 ? (o ? k >> 1 : k & 1) * 64 + j * 16 : j * 32));
                                    bulk_commit();
                                    if (j == 0 && k >= 1 && k < 4) {
                                        bulk_wait<1>();
                                        mbar_arrive(sb + B_ZP + ((k - 1) & 1) * 8);
                                        if (k == 2 && !o) mbar_arrive(sb + B_FA + sw_ * 8);
                                    }
                                }
                                __syncwarp();
                                if (un < 8) __nanosleep(SUB_NS);
                            }
                            __syncwarp();
                        }
                    } else {
                        const uint32_t e = lds16(sb + SM_TAB + (92 + s5_count(0, R.kq) + s5_count(1, R.kq) - 5 - 20) * 2);
                        const uint32_t za = sb + (e & 63) * 4096, zb = sb + ((e >> 6) & 63) * 4096;
#pragma unroll 1
                        for (int k = 0; k < 4; k++) {
                            if (k) mbar_wait(zf + k * 8, k == 1 ? f1 : 0);
                            if (elect_one()) {
                                tma_red2(&P.h_w, (k < 2 ? zb : za) + (k & 1) * 8192, c0 + (k & 1) * 64, r * 128 + (k >> 1) * 64);
                                if (k & 1) tma_red2(&P.h_n, zb + 16384 + (k >> 1) * 4096, g2 * 32, r * 128 + (k >> 1) * 64);
                            }
                            __syncwarp();
                        }
                    }
                }
                __syncwarp();
                if (elect_one()) {
                    bulk_commit();
                    bulk_wait_read<0>();
                    mbar_arrive(sb + B_ZEMPTY + (un & 1) * 8);
                    bulk_wait<0>();
                    if (flag >= 0) { fence_rel(); red_rlx(&P.sm->flags[flag], inc); }
                }
                __syncwarp();
                TR(30 + un);
            }
            if (sw_ == 1 && lane == 0) P.sm->epoch[blockIdx.x] = ep1 + 1;
        }
        cluster_arrive();
        cluster_wait();
    } else if (warp >= 8) {
        asm volatile("setmaxnreg.dec.sync.aligned.u32 40;");
        if (warp != 8) cluster_wait();
#define PIN(v) asm volatile("" : "+r"(v))
        int n = warp == 8 ? 8 : warp - 4;
#pragma unroll 1
        for (; n < 20; n += 4) {
            const int v = n / 5;
            uint32_t st = sb + (n - 5 * v) * 36864 + rho * 8192, bar = sb + B_FULL + (n & 7) * 8;
            int c0 = (n - 5 * v) * 128 + rho * 64, c1 = (sb1 + 4 * v) * 64;
            PIN(st); PIN(bar); PIN(c0); PIN(c1);
            mbar_wait(sb + B_EMPTY + ((n - 5) & 7) * 8, ((n - 5) >> 3) & 1);
            TS(0, n);
            if (elect_one()) {
                mbar_expect_tx(bar, 16384);
                tma_ld2_mc(st, &P.x_a, c0, c1, bar);
            }
            __syncwarp();
            TS(1, n);
        }
        const Role R = get_role(sb, rho);
        const int kq = R.kq, part = kq >> 1, n5 = 92 + s5_count(0, kq), nend = n5 + s5_count(1, kq);
        uint32_t have = 0;
#pragma unroll 1
        for (; n < 52; n += 4) {
            const uint32_t e = lds16(sb + SM_TAB + (n - 20) * 2);
            const int w = n - 1 - ((e >> 12) & 7), m = n - 20;
            uint32_t da = sb + (e & 63) * 4096 + rho * 8192, db = sb + ((e >> 6) & 63) * 4096, bar = sb + B_FULL + (n & 7) * 8;
            int kcol = (kq & 1) * 1024 + (m < 16 ? m : 31 - m) * 64, row = R.ci2 * 256 + rho * 64 + (m >> 4) * 128;
            uint32_t bytes = (e >> 15) ? 36864 : 16384;
            if (m < 16 && !((have >> m) & 1)) have = lds_acq(sb + SM_RDY);
            uint32_t now = (e >> 15) && (m >= 16 || ((have >> m) & 1)) && n != 42;
            PIN(da); PIN(db); PIN(bar); PIN(kcol); PIN(row); PIN(bytes); PIN(now);
            if (n >= 28 && n < 32) mbar_wait(sb + B_S1Z, 0);
            mbar_wait(sb + B_EMPTY + (w & 7) * 8, (w >> 3) & 1);
            TS(0, n);
            if (elect_one()) {
                mbar_expect_tx(bar, bytes);
                tma_ld2_mc(da, &P.ws_a[part], kcol, row, bar);
                if (now) tma_ld2(db, &P.abt_ld, kcol, part * 640 + R.nt2 * 160, bar);
            }
            __syncwarp();
            if (!now && (e >> 15)) {
                if (m < 16) rdy_wait(sb + SM_RDY, 1u << m, have);
                else mbar_wait(sb + B_EMPTY + (38 & 7) * 8, (38 >> 3) & 1);
                if (elect_one()) tma_ld2(db, &P.abt_ld, kcol, part * 640 + R.nt2 * 160, bar);
                __syncwarp();
            }
            if (m == 0) TR(20);
            TS(1, n);
        }
        const CUtensorMap* wmap = rho ? &P.wu_b : &P.wg_b;
#pragma unroll 1
        for (; n < 92; n += 4) {
            const uint32_t e = lds16(sb + SM_TAB + (n - 20) * 2);
            const int w = n - 1 - ((e >> 12) & 7);
            const int u = (n - 52) / 10, j = n - 52 - 10 * u;
            const bool half = s4_half(R.p4, u);
            uint32_t da = sb + (e & 63) * 4096, db = sb + ((e >> 6) & 63) * 4096 + rho * 8192, bar = sb + B_FULL + (n & 7) * 8;
            int kc = (int)((0x7296418530ull >> (4 * ((u & 1) ? 9 - j : j))) & 15) * 64, col = s4_chunk(R.p4, u, R.sig) * 64, hrow = (2 * R.c4 + (u >> 1)) * 128 + (half ? R.sig * 64 : 0);
            uint32_t bytes = (e >> 15) ? (half ? 24576 : 32768) : 16384;
            const uint32_t need = j < 4 ? 1 : 2;
            uint32_t now = (e >> 15) && (j >= 8 || (u & 1) || (lds_acq(sb + SM_RDY + 16 + u * 2) & need));
            uint32_t hoff = half ? 0 : 256;
            PIN(da); PIN(db); PIN(bar); PIN(kc); PIN(col); PIN(hrow); PIN(bytes); PIN(now); PIN(hoff);
            const CUtensorMap* hmap = reinterpret_cast<const CUtensorMap*>(reinterpret_cast<const char*>(&P.h_w) + hoff);
            mbar_wait(sb + B_EMPTY + (w & 7) * 8, (w >> 3) & 1);
            TS(0, n);
            if (elect_one()) {
                mbar_expect_tx(bar, bytes);
                tma_ld2_mc(db, wmap, col, kc, bar);
                if (now) tma_ld2(da, hmap, kc, hrow, bar);
            }
            __syncwarp();
            if (!now && (e >> 15)) {
                have = 0;
                rdy_wait(sb + SM_RDY + 16 + u * 2, need, have, (j & 3) * LAG_NS);
                if (elect_one()) tma_ld2(da, hmap, kc, hrow, bar);
                __syncwarp();
            }
            if (j == 0 && !(u & 1)) TR(21 + (u >> 1));
            TS(1, n);
        }
#pragma unroll 1
        for (; n < nend; n += 4) {
            const uint32_t e = lds16(sb + SM_TAB + (n - 20) * 2);
            const int w = n - 1 - ((e >> 12) & 7), u = n >= n5;
            const int kt = s5_tile(u, kq, n - (u ? n5 : 92));
            uint32_t da = sb + (e & 63) * 4096 + rho * 8192, db = sb + ((e >> 6) & 63) * 4096, bar = sb + B_FULL + (n & 7) * 8;
            int kc = kt * 64, row = R.ci * 256 + rho * 64 + u * 128;
            uint32_t ld2 = e >> 15, now = (lds_acq(sb + SM_RDY + 8 + u * 4) >> kt) & 1;
            PIN(da); PIN(db); PIN(bar); PIN(kc); PIN(row); PIN(ld2); PIN(now);
            mbar_wait(sb + B_EMPTY + (w & 7) * 8, (w >> 3) & 1);
            TS(0, n);
            if (elect_one()) {
                mbar_expect_tx(bar, ld2 ? 40960 : 16384);
                if (now) tma_ld2_mc(da, &P.act_m, kc, row, bar);
                if (ld2) {
                    tma_ld3(db, &P.wdn_w, 0, kc, (R.nt * 5 + 1) >> 1, bar);
                    tma_ld3(db + 16384, &P.wdn_n, 0, kc, R.nt * 5 + (rho ? 0 : 4), bar);
                }
            }
            __syncwarp();
            if (!now) {
                have = 0;
                rdy_wait(sb + SM_RDY + 8 + u * 4, 1u << kt, have);
                if (elect_one()) tma_ld2_mc(da, &P.act_m, kc, row, bar);
                __syncwarp();
            }
            TS(1, n);
        }
        cluster_arrive();
        cluster_wait();
    } else {
        const int wg = warp >> 2, wq = warp & 3;
        const bool t0 = (threadIdx.x & 127) == 0;
        const uint32_t my_ord = sb + B_ORD + wg * 8;
        const uint32_t dummy = sb + B_DUMMY - 64, ct = sb + SM_CT, zf = sb + B_ZFULL + wg * 16;
        const uint32_t rowoff = (wq * 16 + ((lane >> 3) & 1) * 8 + (lane & 7)) * 128, sw = (((lane >> 4) ^ (lane & 7)) << 4);
        const int srow = wq * 16 + (lane >> 2);
        if (wg == 1) {
            {
                cluster_wait();
                mbar_wait(sb + B_SIDE, 0);
                TRW(28);
                const uint32_t a = sb + ZS + wq * 5120 + (lane >> 3) * 1280 + (lane & 7) * 16;
                float ds[4] = {0.f, 0.f, 0.f, 0.f}, dw[4] = {0.f, 0.f, 0.f, 0.f}, d1[4] = {0.f, 0.f, 0.f, 0.f}, d2[4] = {0.f, 0.f, 0.f, 0.f};
                float d3[4] = {0.f, 0.f, 0.f, 0.f}, d4[4] = {0.f, 0.f, 0.f, 0.f};
                uint4 xv[10], wv[10];
#pragma unroll
                for (int k = 0; k < 10; k++) { xv[k] = lds4(a + 20480 + k * 128); wv[k] = lds4(a + k * 128); }
#pragma unroll
                for (int k = 0; k < 10; k++) {
                    hmma16(ds, xv[k], 0x3f803f80u);
                    hmma8(d1, xv[k].x, xv[k].y, xv[k].x); hmma8(d2, xv[k].x, xv[k].y, xv[k].y);
                    hmma8(d3, xv[k].z, xv[k].w, xv[k].z); hmma8(d4, xv[k].z, xv[k].w, xv[k].w);
                    hmma16(dw, wv[k], 0x3f803f80u);
                }
                float s = ds[0] + ds[2], w = dw[0] + dw[2];
                float q = (lane & 4) ? (d1[1] + d2[3]) + (d3[1] + d4[3]) : (d1[0] + d2[2]) + (d3[0] + d4[2]);
                q = __shfl_sync(0xffffffffu, q, (lane & 28) | (lane >> 3));
                s += __shfl_xor_sync(0xffffffffu, s, 4); w += __shfl_xor_sync(0xffffffffu, w, 4); q += __shfl_xor_sync(0xffffffffu, q, 4);
                const float m = s * (1.f / D_);
                const float2 st = ln_coef(m, fmaf(-m, m, q * (1.f / D_)));
                if ((lane & 7) == 0) {
                    const int rr = wq * 4 + (lane >> 3);
                    st_tag2(P.sm->st1 + blockIdx.x * 16 + rr, st, ep1);
                    if (wq < 3) st_tag1(&P.sm->rs[blockIdx.x * 16 + rr], w, ep1);
                }
            }
            if (lane == 0) mbar_arrive(sb + B_GATE);
            TRW(1);
        }

        if (wg == 0) { cluster_wait(); mbar_wait(sb + B_GATE, 0); }
#pragma unroll 1
        for (int i = 0; i < 2; i++) {
            const int v = 2 * i + wg;
            float a[40];
            uint32_t prev = dummy;
            mainloop<80, 0, true>(a, a, ct + v * 80, ct + v * 80 + 80, prev, my_ord, v ? (i + wg - 1) & 1 : -1, t0, lane, v == 0 ? 2 : 3, trp);
            if (v == 0 || v == 3) TRW(4 + wg);
            if (wq == 0 && (v == 1 || v == 2)) XT(8 + v);
            mbar_wait(sb + B_STAT + i * 8, 0);
            z_acquire(sb, v - 2);
            const float sgn = p >= 4 ? -1.f : 1.f;
            float2 s0 = lds2(sb + SM_STATS + (v * 64 + srow) * 8), s1 = lds2(sb + SM_STATS + (v * 64 + srow + 8) * 8);
            s0.x *= sgn; s1.x *= sgn;
            const uint32_t z = sb + ZS + wg * 10240 + ((lane >> 4) * 8 + (lane & 7)) * 128 + (((2 * wq + ((lane >> 3) & 1)) ^ (lane & 7)) << 4);
#pragma unroll
            for (int j = 0; j < 10; j += 2) {
                const float2 ra = lds2(sb + SM_RS + (8 * j + 2 * (lane & 3)) * 4), rb = lds2(sb + SM_RS + (8 * j + 8 + 2 * (lane & 3)) * 4);
                stsm4t(z + j * 1024,
                       pack2(fmaf(s0.y, ra.x, a[4 * j]) * s0.x, fmaf(s0.y, ra.y, a[4 * j + 1]) * s0.x),
                       pack2(fmaf(s1.y, ra.x, a[4 * j + 2]) * s1.x, fmaf(s1.y, ra.y, a[4 * j + 3]) * s1.x),
                       pack2(fmaf(s0.y, rb.x, a[4 * j + 4]) * s0.x, fmaf(s0.y, rb.y, a[4 * j + 5]) * s0.x),
                       pack2(fmaf(s1.y, rb.x, a[4 * j + 6]) * s1.x, fmaf(s1.y, rb.y, a[4 * j + 7]) * s1.x));
            }
            z_publish(zf, 0, lane);
            if (v == 0 || v == 3) TRW(6 + wg);
            if (wq == 0 && (v == 1 || v == 2)) XT(10 + v);
        }
        asm volatile("setmaxnreg.inc.sync.aligned.u32 208;");
        const Role R = get_role(sb, rho);
        {
            float a0[80], a1[80];
            if (wg == 1) mbar_wait(sb + B_S1Z, 0);
            uint32_t prev = dummy;
            const uint32_t te = ct + 576 + wg * 256;
            mainloop<160, 0, false, true>(a0, a1, ct + 320 + wg * 256, te, prev, my_ord, wg ^ 1, t0, lane, 8 + wg, trp);
            tail160<0>(a0, a1, te, prev, sb, 2 + wg, wg, sb + ZB, sb + ZB, wg ? sb + B_ZEMPTY : sb + B_HIZ, 0, my_ord, t0, lane, rowoff, sw, 10 + wg, trp);
            TRW(12 + wg);
        }
        mbar_wait(sb + B_CS, 0);
        const uint32_t zero = P.zero;
#pragma unroll 1
        for (int rb = 0; rb < 2; rb++) {
            const int u = 2 * rb + wg;
            const bool half = s4_half(R.p4, u);
            const float2* csp = reinterpret_cast<const float2*>(P.sm->colsum + s4_chunk(R.p4, u, R.sig) * 64) + (lane & 3);
            float2 cg[8], cu[8];
#pragma unroll
            for (int j = 0; j < 8; j++) { cg[j] = __ldcg(csp + 4 * j); cu[j] = __ldcg(csp + F_ / 2 + 4 * j); }
            float a0[64], a1[64];
            const uint32_t tp = ct + (52 + u * 10) * 16;
            if (half) mainloop_half(a0, tp, dummy, my_ord, (wg + rb) & 1, t0, lane, 40 + u, trp);
            else { uint32_t prev = dummy; mainloop<128, 1>(a0, a1, tp, tp + 160, prev, my_ord, (wg + rb) & 1, t0, lane, 40 + u, trp); }
            TRW(44 + u);
            mbar_wait(sb + B_ST2 + rb * 8, 0);
            z_acquire(sb, 4 + u);
            const uint32_t st = sb + SM_STATS + rb * 1024 + ((half ? R.sig * 64 : 0) + srow) * 8;
            epi_geglu(a0, cg, cu, lds2(st), lds2(st + 64), sb + ZB + rowoff, sw, zero);
            z_publish(zf, 0, lane);
            if (!half) epi_geglu(a1, cg, cu, lds2(st + 512), lds2(st + 576), sb + ZB + 8192 + rowoff, sw, zero);
            z_publish(zf, 1, lane);
            TRW(48 + u);
        }
        {
            float a0[80], a1[80];
            const uint32_t t5 = ct + (92 + s5_count(0, R.kq)) * 16;
            uint32_t prev = dummy;
            const uint32_t te = (wg ? t5 + s5_count(1, R.kq) * 16 : t5) - 48;
            mainloop<160, 1, false, true>(a0, a1, wg ? t5 : ct + 92 * 16, te, prev, my_ord, wg, t0, lane, 14 + wg, trp);
            uint32_t za = sb + ZB, zb = za, zbar = sb + B_ZEMPTY + 8, zpar = 0;
            if (wg == 1) {
                const int nl = 92 + s5_count(0, R.kq) + s5_count(1, R.kq) - 5;
                const uint32_t e = lds16(sb + SM_TAB + (nl - 20) * 2);
                zbar = sb + B_EMPTY + (nl & 7) * 8; zpar = (nl >> 3) & 1;
                za = sb + (e & 63) * 4096; zb = sb + ((e >> 6) & 63) * 4096;
            }
            tail160<1>(a0, a1, te, prev, sb, 8 + wg, 2 + wg, za, zb, zbar, zpar, my_ord, t0, lane, rowoff, sw, 16 + wg, trp);
            TRW(18 + wg);
        }
        cluster_arrive();
        cluster_wait();
    }
}

__global__ void fb_ln(const __nv_bfloat16* x, __nv_bfloat16* y) {
    const int row = blockIdx.x * 8 + (threadIdx.x >> 5), lane = threadIdx.x & 31;
    float v[20], s = 0.f, q = 0.f;
    for (int k = 0; k < 20; k++) { v[k] = __bfloat162float(x[row * D_ + k * 32 + lane]); s += v[k]; }
    for (int o = 16; o; o >>= 1) s += __shfl_xor_sync(0xffffffffu, s, o);
    s *= 1.f / D_;
    for (int k = 0; k < 20; k++) q += (v[k] - s) * (v[k] - s);
    for (int o = 16; o; o >>= 1) q += __shfl_xor_sync(0xffffffffu, q, o);
    const float r = rsqrtf(q * (1.f / D_) + LN_EPS);
    for (int k = 0; k < 20; k++) y[row * D_ + k * 32 + lane] = __float2bfloat16((v[k] - s) * r);
}
__global__ void fb_gemm(const __nv_bfloat16* A0, const __nv_bfloat16* B0, const __nv_bfloat16* A1, const __nv_bfloat16* B1, int K, int bk,
                        int bn, int N, const __nv_bfloat16* add, __nv_bfloat16* C, int mode) {
    __shared__ float sa[2][16][17], sbm[2][16][17];
    const int tx = threadIdx.x & 15, ty = threadIdx.x >> 4, m = blockIdx.y * 16 + ty, n = blockIdx.x * 16 + tx;
    const bool two = mode == 1 || mode == 2;
    float c0 = 0.f, c1 = 0.f;
    for (int k0 = 0; k0 < K; k0 += 16) {
        sa[0][ty][tx] = __bfloat162float(A0[(size_t)m * K + k0 + tx]);
        sbm[0][ty][tx] = __bfloat162float(B0[(size_t)(k0 + ty) * bk + (size_t)n * bn]);
        if (two) {
            sa[1][ty][tx] = __bfloat162float(A1[(size_t)m * K + k0 + tx]);
            sbm[1][ty][tx] = __bfloat162float(B1[(size_t)(k0 + ty) * bk + (size_t)n * bn]);
        }
        __syncthreads();
        for (int k = 0; k < 16; k++) { c0 += sa[0][ty][k] * sbm[0][k][tx]; if (two) c1 += sa[1][ty][k] * sbm[1][k][tx]; }
        __syncthreads();
    }
    float r = c0;
    if (mode == 1) r = __bfloat162float(add[(size_t)m * N + n]) + c0 - c1;
    if (mode == 2) r = 0.5f * c0 * (1.f + tanhf(0.7978845608028654f * (c0 + 0.044715f * c0 * c0 * c0))) * c1;
    if (mode == 3) r = __bfloat162float(add[(size_t)m * N + n]) + c0;
    C[(size_t)m * N + n] = __float2bfloat16(r);
}

typedef CUresult (*EncodeFn)(CUtensorMap*, CUtensorMapDataType, cuuint32_t, void*, const cuuint64_t*, const cuuint64_t*, const cuuint32_t*,
                             const cuuint32_t*, CUtensorMapInterleave, CUtensorMapSwizzle, CUtensorMapL2promotion, CUtensorMapFloatOOBfill);

void map2(EncodeFn enc, CUtensorMap* m, const void* ptr, uint64_t cols, uint64_t rows, uint32_t brows) {
    cuuint64_t gd[2] = {cols, rows}, gs[1] = {cols * 2};
    cuuint32_t bd[2] = {64, brows}, es[2] = {1, 1};
    enc(m, CU_TENSOR_MAP_DATA_TYPE_BFLOAT16, 2, const_cast<void*>(ptr), gd, gs, bd, es, CU_TENSOR_MAP_INTERLEAVE_NONE,
        CU_TENSOR_MAP_SWIZZLE_128B, CU_TENSOR_MAP_L2_PROMOTION_L2_128B, CU_TENSOR_MAP_FLOAT_OOB_FILL_NONE);
}
void map2n(EncodeFn enc, CUtensorMap* m, const void* ptr, uint32_t brows) {
    cuuint64_t gd[2] = {640, 2048}, gs[1] = {1280};
    cuuint32_t bd[2] = {32, brows}, es[2] = {1, 1};
    enc(m, CU_TENSOR_MAP_DATA_TYPE_BFLOAT16, 2, const_cast<void*>(ptr), gd, gs, bd, es, CU_TENSOR_MAP_INTERLEAVE_NONE,
        CU_TENSOR_MAP_SWIZZLE_64B, CU_TENSOR_MAP_L2_PROMOTION_L2_128B, CU_TENSOR_MAP_FLOAT_OOB_FILL_NONE);
}
void map3w(EncodeFn enc, CUtensorMap* m, const void* ptr, uint64_t rows, uint32_t brows = 64) {
    cuuint64_t gd[3] = {64, rows, 10}, gs[2] = {1280, 128};
    cuuint32_t bd[3] = {64, brows, 2}, es[3] = {1, 1, 1};
    enc(m, CU_TENSOR_MAP_DATA_TYPE_BFLOAT16, 3, const_cast<void*>(ptr), gd, gs, bd, es, CU_TENSOR_MAP_INTERLEAVE_NONE,
        CU_TENSOR_MAP_SWIZZLE_128B, CU_TENSOR_MAP_L2_PROMOTION_L2_128B, CU_TENSOR_MAP_FLOAT_OOB_FILL_NONE);
}
void map3n(EncodeFn enc, CUtensorMap* m, const void* ptr, uint64_t rows) {
    cuuint64_t gd[3] = {32, rows, 20}, gs[2] = {1280, 64};
    cuuint32_t bd[3] = {64, 64, 1}, es[3] = {1, 1, 1};
    enc(m, CU_TENSOR_MAP_DATA_TYPE_BFLOAT16, 3, const_cast<void*>(ptr), gd, gs, bd, es, CU_TENSOR_MAP_INTERLEAVE_NONE,
        CU_TENSOR_MAP_SWIZZLE_128B, CU_TENSOR_MAP_L2_PROMOTION_L2_128B, CU_TENSOR_MAP_FLOAT_OOB_FILL_NONE);
}

}

extern "C" void kernel_launch(void* const* d_in, const int* in_sizes, int n_in, void* d_out, int out_size) {
    static EncodeFn enc = nullptr;
    static void *abt, *act, *sm;
    static int fits = -1;
    typedef const __nv_bfloat16* BP;
    cudaLaunchConfig_t cfg = {};
    cfg.gridDim = dim3(NCTA);
    cfg.blockDim = dim3(512);
    cfg.dynamicSmemBytes = SMEM_BYTES;
    cfg.stream = cudaStreamPerThread;
    if (fits < 0) {
        void* fn = nullptr;
        cudaDriverEntryPointQueryResult st;
        cudaGetDriverEntryPoint("cuTensorMapEncodeTiled", &fn, cudaEnableDefault, &st);
        enc = (EncodeFn)fn;
        cudaGetSymbolAddress(&abt, g_abt);
        cudaGetSymbolAddress(&sm, g_small);
        cudaGetSymbolAddress(&act, g_act);
        cudaFuncSetAttribute(fused_kernel, cudaFuncAttributeMaxDynamicSharedMemorySize, SMEM_BYTES);
        int nc = 0;
        cudaLaunchAttribute at;
        at.id = cudaLaunchAttributeClusterDimension;
        at.val.clusterDim.x = 2; at.val.clusterDim.y = 1; at.val.clusterDim.z = 1;
        cudaLaunchConfig_t q = cfg;
        q.attrs = &at; q.numAttrs = 1;
        fits = enc && cudaOccupancyMaxActiveClusters(&nc, fused_kernel, &q) == cudaSuccess && nc >= NCTA / 2;
        cudaGetLastError();
    }
    if (!fits) {
        cudaStream_t s = cudaStreamPerThread;
        __nv_bfloat16 *a = (__nv_bfloat16*)abt, *b = a + S_ * D_, *t = (__nv_bfloat16*)act, *o = (__nv_bfloat16*)d_out;
        fb_ln<<<S_ / 8, 256, 0, s>>>((BP)d_in[0], t);
        fb_gemm<<<dim3(D_ / 16, S_ / 16), 256, 0, s>>>(t, (BP)d_in[3], nullptr, nullptr, D_, 1, D_, D_, nullptr, a, 0);
        fb_gemm<<<dim3(D_ / 16, S_ / 16), 256, 0, s>>>(t, (BP)d_in[4], nullptr, nullptr, D_, 1, D_, D_, nullptr, b, 0);
        fb_gemm<<<dim3(D_ / 16, S_ / 16), 256, 0, s>>>((BP)d_in[1], a, (BP)d_in[2], b, S_, D_, 1, D_, (BP)d_in[0], o, 1);
        fb_ln<<<S_ / 8, 256, 0, s>>>(o, a);
        fb_gemm<<<dim3(F_ / 16, S_ / 16), 256, 0, s>>>(a, (BP)d_in[6], a, (BP)d_in[7], D_, F_, 1, F_, nullptr, t, 2);
        fb_gemm<<<dim3(D_ / 16, S_ / 16), 256, 0, s>>>(t, (BP)d_in[8], nullptr, nullptr, F_, D_, 1, D_, o, o, 3);
        return;
    }
    Params P;
    P.x = (BP)d_in[0]; P.wd[0] = (BP)d_in[3]; P.wd[1] = (BP)d_in[4];
    P.wg = (BP)d_in[6]; P.wu = (BP)d_in[7]; P.wdn = (BP)d_in[8]; P.out = (__nv_bfloat16*)d_out;
    P.sm = (Small*)sm; P.zero = 0;
    void* h = d_out;
    map2(enc, &P.x_a, P.x, D_, S_, 64);
    map3w(enc, &P.wd_b[0], P.wd[0], D_, 80);
    map3w(enc, &P.wd_b[1], P.wd[1], D_, 80);
    map2(enc, &P.abt_st, abt, S_, 1280, 16);
    map2(enc, &P.abt_ld, abt, S_, 1280, 160);
    map2(enc, &P.ws_a[0], d_in[1], S_, S_, 64);
    map2(enc, &P.ws_a[1], d_in[2], S_, S_, 64);
    map2(enc, &P.h_w, h, D_, S_, 64);
    map2n(enc, &P.h_n, h, 64);
    map2n(enc, &P.h_sn, h, 32);
    map2(enc, &P.h_sw, h, D_, S_, 16);
    map2(enc, &P.act_s, act, F_, S_, 16);
    map2(enc, &P.h_l, h, D_, S_, 128);
    map2(enc, &P.wg_b, P.wg, F_, D_, 64);
    map2(enc, &P.wu_b, P.wu, F_, D_, 64);
    map2(enc, &P.act_m, act, F_, S_, 64);
    map3w(enc, &P.wdn_w, P.wdn, F_);
    map3n(enc, &P.wdn_n, P.wdn, F_);
    cudaLaunchKernelEx(&cfg, fused_kernel, P);
}
```
